```python
import torch

def _softmax(x, axis=-1):
    return torch.softmax(x, dim=axis)
def _gelu(x):
    return torch.nn.functional.gelu(x, approximate="tanh")
def _silu(x):
    return torch.nn.functional.silu(x)
def _sigmoid(x):
    return torch.sigmoid(x)
def _layernorm(x, axis=-1, eps=1e-5):
    m = x.mean(dim=axis, keepdim=True)
    v = x.var(dim=axis, keepdim=True, unbiased=False)
    return (x - m) / torch.sqrt(v + eps)
def _scatter_add(tgt, idx, src, axis=0):
    return tgt.clone().index_add_(axis, idx, src)
def _segment_sum(src, seg, n):
    out = torch.zeros((n,) + src.shape[1:], dtype=src.dtype)
    return out.index_add_(0, seg, src)
def _pad(x, pw):
    flat = tuple(v for pair in reversed(pw) for v in pair)
    return torch.nn.functional.pad(x, flat)

kernel_name = 'standalone__mpnn_edge_mlp__graph'

def setup_inputs():

    _w = (lambda a: (lambda t: t.to(torch.bfloat16) if t.is_floating_point() else t)(torch.as_tensor(a)))
    N, deg, D, De = 25000, 16, 128, max(4, 1)
    E = N * deg
    return {
        "x": _w((lambda *s: torch.randn(*s, dtype=torch.bfloat16) * 0.05)(N, D)),
        "e_attr": _w((lambda *s: torch.randn(*s, dtype=torch.bfloat16) * 0.4)(E, De)),
        "src": _w((lambda lo, hi, *s: torch.randint(lo, hi, s))(0, N, E).to(torch.int64)),
        "dst": _w((lambda lo, hi, *s: torch.randint(lo, hi, s))(0, N, E).to(torch.int64)),
        "w_msg": _w((lambda *s: torch.randn(*s, dtype=torch.bfloat16) * 0.4)(2 * D + De, D)),
        "w_upd": _w((lambda *s: torch.randn(*s, dtype=torch.bfloat16) * 0.05)(2 * D, D)),
    }

def reference(x, e_attr, src, dst, w_msg, w_upd):
    N, D = x.shape
    m_in = torch.concatenate([x[src], x[dst], e_attr], axis=-1)
    msg = _silu(m_in @ w_msg)
    agg = _segment_sum(msg, dst, N)
    return _silu(torch.concatenate([x, agg], axis=-1) @ w_upd)
```

```cpp
#include <cuda.h>
#include <cuda_runtime.h>
#include <cuda_bf16.h>
#include <cuda_fp16.h>
#include <stdint.h>
#include <type_traits>

namespace {

constexpr int NN = 25000, NE = 400000;
constexpr int NCTA = 132, NT = 190;
constexpr int CH = 3032;
constexpr int CHP = 3040;
constexpr int OFFS = 136;
constexpr int RCAP = 3520;
constexpr int NTHR = 768;
constexpr int SPIN = 1 << 20;
constexpr int NULLROW = 25088;
constexpr int LBO = 3216;
enum { EV_SRC, EV_E, EV_W1 = EV_E + 2, EV_WT, EV_W2, EV_X, EV_PFE = EV_X + 3, EV_PFX = EV_PFE + 4, EV_END = EV_PFX + 12 };
struct Sched { uint32_t ev[32], t_off, t_rec, t_e; };

constexpr int S_U = 0;
constexpr int S_RING = 49152;
constexpr int S_WB = S_RING + 49152;
constexpr int S_Q = S_WB + 32768;
constexpr int S_RAWE = S_Q + 16 * LBO - CH * 8;
constexpr int S_RE = S_Q + 16 * LBO;
constexpr int S_RM = S_RE + RCAP * 8;
constexpr int S_W3 = S_RM + RCAP * 4;
constexpr int S_HIST = S_W3 + 1024;
constexpr int S_H2 = S_HIST + 640;
constexpr int S_MISC = S_H2 + 1024;
constexpr int S_ENT = S_MISC + 64;
constexpr int S_OFA = S_ENT + 640;
constexpr int S_ST = S_OFA + 1056;
constexpr int S_TAB = S_ST + 1024;
constexpr int S_MBAR = S_TAB + 192;
constexpr int S_TIME = S_MBAR + 256;
constexpr int S_TOTAL = S_TIME + 512;
static_assert(S_TOTAL <= 232448, "smem");
static_assert(S_RAWE >= S_Q + 8 * LBO && S_RAWE % 16 == 0, "raw e_attr must stay clear of Q half 0");
enum { B_DST, B_SRC, B_E, B_W1, B_WT, B_W2, B_X, B_GO = B_X + 3, B_SCAN, B_W3, B_X2FREE, B_DSFREE, B_EFREE, B_WBFREE, B_PDONE, B_JOIN, B_NUM };

constexpr uint32_t G_P = 0;
constexpr uint32_t G_RM = 0x630000;
constexpr uint32_t G_RE = 0x7C0000;
constexpr uint32_t G_OFF = 0xAD0000;
constexpr uint32_t G_CNT = 0xAF8000;
__device__ uint4 g_scratch[(32u << 20) / 16];

#define STAMP(i)
#define GSTAMP(i)

__device__ __forceinline__ uint32_t smem_u32(const void* p) { return (uint32_t)__cvta_generic_to_shared(p); }
__device__ __forceinline__ int uni(int v) { return __shfl_sync(0xffffffffu, v, 0); }
__device__ __forceinline__ uint32_t opaque(uint32_t v) { return __shfl_sync(0xffffffffu, v, threadIdx.x & 31); }
__device__ __forceinline__ void bar_sync(int id, int n) { asm volatile("bar.sync %0,%1;" ::"r"(id), "r"(n) : "memory"); }
__device__ __forceinline__ uint32_t prmt(uint32_t a, uint32_t b, uint32_t c) {
    uint32_t r; asm("prmt.b32 %0,%1,%2,%3;" : "=r"(r) : "r"(a), "r"(b), "r"(c)); return r;
}
__device__ __forceinline__ uint32_t pack_bf(float lo, float hi) {
    uint32_t r; asm("cvt.rn.bf16x2.f32 %0,%1,%2;" : "=r"(r) : "f"(hi), "f"(lo)); return r;
}
__device__ __forceinline__ uint32_t pack_h(float lo, float hi) {
    uint32_t r; asm("cvt.rn.f16x2.f32 %0,%1,%2;" : "=r"(r) : "f"(hi), "f"(lo)); return r;
}
__device__ __forceinline__ uint32_t bf2_to_h2(uint32_t w) {
    return pack_h(__uint_as_float(w << 16), __uint_as_float(w & 0xffff0000u));
}
__device__ __forceinline__ uint32_t amax_h2(uint32_t a, uint32_t b) {
    uint32_t r; asm("max.NaN.xorsign.abs.f16x2 %0,%1,%2;" : "=r"(r) : "r"(a), "r"(b)); return r;
}
__device__ __forceinline__ uint32_t amax_bf2(uint32_t a, uint32_t b) {
    uint32_t r; asm("max.NaN.xorsign.abs.bf16x2 %0,%1,%2;" : "=r"(r) : "r"(a), "r"(b)); return r;
}
__device__ __forceinline__ uint32_t mag16(uint32_t w) { return max(w & 0x7fffu, (w >> 16) & 0x7fffu); }
__device__ __forceinline__ uint32_t half_bf2(uint32_t a) {
    uint32_t r; asm("mul.rn.bf16x2 %0,%1,%2;" : "=r"(r) : "r"(a), "r"(0x3F003F00u)); return r;
}
__device__ __forceinline__ float tanh_f(float x) { float y; asm("tanh.approx.f32 %0,%1;" : "=f"(y) : "f"(x)); return y; }
__device__ __forceinline__ void stsm4(uint32_t a, uint32_t r0, uint32_t r1, uint32_t r2, uint32_t r3) {
    asm volatile("stmatrix.sync.aligned.m8n8.x4.shared.b16 [%0],{%1,%2,%3,%4};" ::"r"(a), "r"(r0), "r"(r1), "r"(r2), "r"(r3) : "memory");
}
__device__ __forceinline__ uint4 lds128(uint32_t a) {
    uint4 v; asm volatile("ld.shared.v4.u32 {%0,%1,%2,%3},[%4];" : "=r"(v.x), "=r"(v.y), "=r"(v.z), "=r"(v.w) : "r"(a) : "memory"); return v;
}
__device__ __forceinline__ void sts128(uint32_t a, uint32_t x, uint32_t y, uint32_t z, uint32_t w) {
    asm volatile("st.shared.v4.u32 [%0],{%1,%2,%3,%4};" ::"r"(a), "r"(x), "r"(y), "r"(z), "r"(w) : "memory");
}
__device__ __forceinline__ uint32_t ld_rlx(const void* p) {
    uint32_t v; asm volatile("ld.relaxed.gpu.global.u32 %0,[%1];" : "=r"(v) : "l"(p) : "memory"); return v;
}

__device__ __forceinline__ __half2 H2(uint32_t v) { return *(__half2*)&v; }
__device__ __forceinline__ uint32_t U32(__half2 v) { return *(uint32_t*)&v; }
__device__ __forceinline__ uint32_t tanh_h2(uint32_t h) { uint32_t t; asm("tanh.approx.f16x2 %0,%1;" : "=r"(t) : "r"(h)); return t; }
__device__ __forceinline__ void bar_arrive(int id, int n) { asm volatile("bar.arrive %0,%1;" ::"r"(id), "r"(n) : "memory"); }
__device__ __forceinline__ void fence_async() { asm volatile("fence.proxy.async.shared::cta;" ::: "memory"); }
__device__ __forceinline__ void bulk_store(void* g, uint32_t s, int bytes) {
    asm volatile("cp.async.bulk.global.shared::cta.bulk_group [%0],[%1],%2;" ::"l"(g), "r"(s), "r"(bytes) : "memory");
}
__device__ __forceinline__ void bulk_wait() {
    asm volatile("cp.async.bulk.commit_group;" ::: "memory");
    asm volatile("cp.async.bulk.wait_group 0;" ::: "memory");
}
__device__ __forceinline__ void gemm_half(float (&d)[32], const uint32_t (&xa)[8][4], uint32_t bsm) {
    const uint64_t desc = ((uint64_t)1 << 62) | ((uint64_t)64 << 32) | ((uint64_t)1 << 16) | (uint64_t)((bsm & 0x3FFFF) >> 4);
    asm volatile("wgmma.fence.sync.aligned;" ::: "memory");
#pragma unroll
    for (int ks = 0; ks < 8; ks++) {
        asm volatile(
            "{.reg .pred p; setp.ne.b32 p,%37,0;\n"
            "wgmma.mma_async.sync.aligned.m64n64k16.f32.bf16.bf16 "
            "{%0,%1,%2,%3,%4,%5,%6,%7,%8,%9,%10,%11,%12,%13,%14,%15,%16,%17,%18,%19,%20,%21,%22,%23,%24,%25,%26,%27,%28,%29,%30,%31},"
            "{%32,%33,%34,%35},%36,p,1,1,1;}"
            : "+f"(d[0]), "+f"(d[1]), "+f"(d[2]), "+f"(d[3]), "+f"(d[4]), "+f"(d[5]), "+f"(d[6]), "+f"(d[7]),
              "+f"(d[8]), "+f"(d[9]), "+f"(d[10]), "+f"(d[11]), "+f"(d[12]), "+f"(d[13]), "+f"(d[14]), "+f"(d[15]),
              "+f"(d[16]), "+f"(d[17]), "+f"(d[18]), "+f"(d[19]), "+f"(d[20]), "+f"(d[21]), "+f"(d[22]), "+f"(d[23]),
              "+f"(d[24]), "+f"(d[25]), "+f"(d[26]), "+f"(d[27]), "+f"(d[28]), "+f"(d[29]), "+f"(d[30]), "+f"(d[31])
            : "r"(xa[ks][0]), "r"(xa[ks][1]), "r"(xa[ks][2]), "r"(xa[ks][3]), "l"(desc + ks * 128), "r"(ks));
    }
    asm volatile("wgmma.commit_group.sync.aligned;" ::: "memory");
}
__device__ __forceinline__ void gemm_wait(float (&d)[32]) {
    asm volatile("wgmma.wait_group.sync.aligned 0;" ::: "memory");
#pragma unroll
    for (int i = 0; i < 32; i++) asm volatile("" : "+f"(d[i])::"memory");
}
__device__ __forceinline__ void fence_release() { asm volatile("fence.release.gpu;" ::: "memory"); }
__device__ __forceinline__ void fence_acquire() { asm volatile("fence.acquire.gpu;" ::: "memory"); }

__device__ __forceinline__ void mbar_wait(uint32_t bar) {
    uint32_t ok = 0;
    int it = 0;
#pragma unroll 1
    while (!ok && ++it < (1 << 16))
        asm volatile("{.reg .pred p; mbarrier.try_wait.parity.shared::cta.b64 p,[%1],0; selp.u32 %0,1,0,p;}" : "=r"(ok) : "r"(bar) : "memory");
}
__device__ __forceinline__ void mbar_wait_warp(uint32_t bar) { mbar_wait(bar); __syncwarp(); }
__device__ __forceinline__ void grid_arrive(char* scr, int which, int cta) {
    asm volatile("red.release.gpu.global.add.u32 [%0],%1;" ::"l"(scr + G_CNT + (cta & 7) * 128 + which * 4), "r"(cta < 8 ? (cta < 4 ? 16u : 17u) : 1u) : "memory");
}
__device__ __forceinline__ bool grid_wait(const char* scr, int which, uint32_t tag, int lane) {
    int it = 0;
#pragma unroll 1
    while (__any_sync(0xffffffffu, (int)(ld_rlx(scr + G_CNT + (lane & 7) * 128 + which * 4) - (tag << 5)) < 0) && ++it < SPIN) {}
    fence_acquire();
    return it >= SPIN;
}
__device__ __forceinline__ void mbar_expect(uint32_t bar, int bytes) {
    asm volatile("mbarrier.arrive.expect_tx.shared::cta.b64 _,[%0],%1;" ::"r"(bar), "r"(bytes) : "memory");
}
__device__ __forceinline__ void bulk_load(uint32_t s, const void* g, int bytes, uint32_t bar) {
    asm volatile("cp.async.bulk.shared::cluster.global.mbarrier::complete_tx::bytes [%0],[%1],%2,[%3];" ::"r"(s), "l"(g), "r"(bytes), "r"(bar) : "memory");
}
__device__ __forceinline__ void bulk_prefetch(const void* g, int bytes) {
    asm volatile("cp.async.bulk.prefetch.L2.global [%0],%1;" ::"l"(g), "r"(bytes) : "memory");
}
__device__ __forceinline__ void mbar_arrive(uint32_t bar) { asm volatile("mbarrier.arrive.shared::cta.b64 _,[%0];" ::"r"(bar) : "memory"); }
__device__ __forceinline__ void tma_load(uint32_t s, const CUtensorMap* tm, int row, int half, uint32_t bar) {
    asm volatile("cp.async.bulk.tensor.3d.shared::cluster.global.mbarrier::complete_tx::bytes [%0],[%1,{%5,%3,%4}],[%2];"
                 ::"r"(s), "l"(tm), "r"(bar), "r"(row), "r"(half), "r"(0) : "memory");
}
__device__ __forceinline__ void tma_store(const CUtensorMap* tm, uint32_t s, int row, int half) {
    asm volatile("cp.async.bulk.tensor.3d.global.shared::cta.bulk_group [%0,{%4,%2,%3}],[%1];" ::"l"(tm), "r"(s), "r"(row), "r"(half), "r"(0) : "memory");
}
__device__ __forceinline__ void ldsm4(uint32_t (&r)[4], uint32_t a) {
    asm volatile("ldmatrix.sync.aligned.m8n8.x4.shared.b16 {%0,%1,%2,%3},[%4];"
                 : "=r"(r[0]), "=r"(r[1]), "=r"(r[2]), "=r"(r[3]) : "r"(a) : "memory");
}
__device__ __forceinline__ uint4 ldg128(const void* p) {
    uint4 v; asm volatile("ld.global.nc.L1::no_allocate.v4.u32 {%0,%1,%2,%3},[%4];" : "=r"(v.x), "=r"(v.y), "=r"(v.z), "=r"(v.w) : "l"(p) : "memory"); return v;
}
__device__ __forceinline__ uint2 lds64(uint32_t a) {
    uint2 v; asm volatile("ld.shared.v2.u32 {%0,%1},[%2];" : "=r"(v.x), "=r"(v.y) : "r"(a) : "memory"); return v;
}
__device__ __forceinline__ void sts32(uint32_t a, uint32_t v) { asm volatile("st.shared.u32 [%0],%1;" ::"r"(a), "r"(v) : "memory"); }
__device__ __forceinline__ void sts64(uint32_t a, uint32_t x, uint32_t y) { asm volatile("st.shared.v2.u32 [%0],{%1,%2};" ::"r"(a), "r"(x), "r"(y) : "memory"); }
__device__ __forceinline__ uint32_t atoms_inc(uint32_t a) {
    uint32_t r; asm volatile("atom.shared.add.u32 %0,[%1],1;" : "=r"(r) : "r"(a) : "memory"); return r;
}
__device__ __forceinline__ uint32_t lds32(uint32_t a) {
    uint32_t v; asm volatile("ld.shared.u32 %0,[%1];" : "=r"(v) : "r"(a) : "memory"); return v;
}

__device__ __noinline__ void generic_path(char* smem, const __nv_bfloat16* __restrict__ x, const __nv_bfloat16* __restrict__ ea,
                                          const int* __restrict__ src, const int* __restrict__ dst,
                                          const __nv_bfloat16* __restrict__ wm, const __nv_bfloat16* __restrict__ wu,
                                          __nv_bfloat16* __restrict__ out) {
    float* agg = (float*)smem;
    __nv_bfloat16* w = (__nv_bfloat16*)(smem + NT * 512);
    int* list = (int*)(smem + NT * 512 + 260 * 256);
    int* cnt = list + NTHR;
    const int tid = threadIdx.x, f = tid & 127, sub = tid >> 7, n0 = blockIdx.x * NT;
    __syncthreads();
    for (int i = tid; i < NT * 128; i += NTHR) agg[i] = 0.f;
    for (int i = tid; i < 260 * 128; i += NTHR) w[i] = wm[i];
    for (int base = 0; base < NE; base += NTHR) {
        if (tid == 0) *cnt = 0;
        __syncthreads();
        const int e = base + tid;
        if (e < NE && (unsigned)(dst[e] - n0) < (unsigned)NT) list[atomicAdd(cnt, 1)] = e;
        __syncthreads();
        const int n = *cnt;
        for (int i = sub; i < n; i += NTHR / 128) {
            const int ee = list[i], s = src[ee], d = dst[ee];
            float z = 0.f;
            for (int k = 0; k < 128; k++) {
                z = fmaf(__bfloat162float(x[s * 128 + k]), __bfloat162float(w[k * 128 + f]), z);
                z = fmaf(__bfloat162float(x[d * 128 + k]), __bfloat162float(w[(128 + k) * 128 + f]), z);
            }
            for (int k = 0; k < 4; k++) z = fmaf(__bfloat162float(ea[ee * 4 + k]), __bfloat162float(w[(256 + k) * 128 + f]), z);
            atomicAdd(&agg[(d - n0) * 128 + f], z / (1.f + expf(-z)));
        }
        __syncthreads();
    }
    for (int i = tid; i < 256 * 128; i += NTHR) w[i] = wu[i];
    __syncthreads();
    for (int r = sub; r < NT && n0 + r < NN; r += NTHR / 128) {
        float z = 0.f;
        for (int k = 0; k < 128; k++) {
            z = fmaf(__bfloat162float(x[(n0 + r) * 128 + k]), __bfloat162float(w[k * 128 + f]), z);
            z = fmaf(agg[r * 128 + k], __bfloat162float(w[(128 + k) * 128 + f]), z);
        }
        out[(n0 + r) * 128 + f] = __float2bfloat16(z / (1.f + expf(-z)));
    }
}

__global__ void __launch_bounds__(NTHR, 1)
mpnn_kernel(const __nv_bfloat16* __restrict__ x, const __nv_bfloat16* __restrict__ ea, const int* __restrict__ src,
            const int* __restrict__ dst, const __nv_bfloat16* __restrict__ wm, const __nv_bfloat16* __restrict__ wu,
            __nv_bfloat16* __restrict__ out, char* const scr, const __grid_constant__ Sched sched, const __grid_constant__ CUtensorMap tm_msg,
            const __grid_constant__ CUtensorMap tm_upd, const __grid_constant__ CUtensorMap tm_x, const __grid_constant__ CUtensorMap tm_p) {
    extern __shared__ __align__(1024) char smem[];
    const uint32_t t_start = (uint32_t)clock();
    const uint32_t sb = smem_u32(smem), mb = sb + S_MBAR;
    const int cta = uni(blockIdx.x), n0 = cta * NT;
    const int nv = min(NT, NN - n0);
    const int n2 = min(CH, NE - cta * CH) >> 1;
    if (threadIdx.x == 256) {
        asm volatile("mbarrier.init.shared::cta.b64 [%0],1;" ::"r"(mb + B_DST * 8) : "memory");
        asm volatile("fence.mbarrier_init.release.cluster;" ::: "memory");
        mbar_expect(mb + B_DST * 8, n2 * 8);
        bulk_load(sb + S_Q, dst + cta * CH, n2 * 8, mb + B_DST * 8);
        bulk_prefetch(src + cta * CH, 128);
        bulk_prefetch(x + n0 * 128, 128);
        bulk_prefetch(ea + cta * CH * 4, 128);
#pragma unroll
        for (int i = 1; i < B_NUM; i++)
            asm volatile("mbarrier.init.shared::cta.b64 [%0],%1;" ::"r"(mb + i * 8), "r"(i == B_JOIN ? 24 : i >= B_DSFREE ? 12 : i >= B_W3 ? 4 : 1) : "memory");
        asm volatile("fence.mbarrier_init.release.cluster;" ::: "memory");
    } else if (threadIdx.x >= 336) {
        ((int*)(smem + S_HIST))[threadIdx.x - 336] = 0;
    }
    const int tid = opaque(threadIdx.x), lane = tid & 31;
    const int warp = uni(threadIdx.x >> 5);
    volatile int* misc = (volatile int*)(smem + S_MISC);
    bool bad = false;
    if (tid == 0) { STAMP(0); GSTAMP(0); }
    __syncthreads();

    if (warp < 12) {
        asm volatile("setmaxnreg.inc.sync.aligned.u32 96;");
        const int wg = warp >> 2;
        if (tid == 256) {
            mbar_expect(mb + B_E * 8, n2 * 16);
            if (cta < 32) bulk_prefetch(cta < 16 ? wm + cta * 16 * 128 : wu + (cta - 16) * 16 * 128, 4096);
#pragma unroll 1
            for (int i = 0; i < 32; i++) {
                const uint32_t v = sched.ev[i], e = v & 255;
                if (e == EV_END) break;
                while ((uint32_t)clock() - t_start < (v >> 8)) {}
                if (e == EV_SRC) {
                    mbar_expect(mb + B_SRC * 8, n2 * 8);
                    bulk_load(sb + S_Q + 12288, src + cta * CH, n2 * 8, mb + B_SRC * 8);
                } else if (e < EV_W1) {
                    const int k = e - EV_E;
                    bulk_load(sb + S_RAWE + k * 12288, ea + cta * CH * 4 + k * 6144, k ? n2 * 16 - 12288 : 12288, mb + B_E * 8);
                } else if (e < EV_X) {
                    const uint32_t bar = mb + (B_W1 + e - EV_W1) * 8;
                    mbar_expect(bar, 32768);
                    tma_load(sb + (e == EV_W1 ? S_U + 32768 : e == EV_WT ? S_WB + 16384 : S_RING + 16384), e == EV_WT ? &tm_upd : &tm_msg, e == EV_W2 ? 128 : 0, 0, bar);
                    tma_load(sb + (e == EV_W1 ? S_WB : e == EV_WT ? S_RING : S_RING + 32768), e == EV_WT ? &tm_upd : &tm_msg, e == EV_W2 ? 128 : 0, 1, bar);
                } else if (e < EV_PFE) {
                    const int k = e - EV_X;
                    if (k == 2) mbar_wait(mb + B_DSFREE * 8);
                    mbar_expect(mb + (B_X + k) * 8, 16384);
                    tma_load(sb + (k < 2 ? S_U + k * 16384 : S_Q), &tm_x, n0 + k * 64, 0, mb + (B_X + k) * 8);
                } else if (e < EV_PFX) {
                    const int k = e - EV_PFE;
                    bulk_prefetch(ea + cta * CH * 4 + k * 3072, k < 3 ? 6144 : n2 * 16 - 18432);
                } else {
                    const int k = e - EV_PFX;
                    if (nv > k * 16) bulk_prefetch(x + (n0 + k * 16) * 128, min(16, nv - k * 16) * 256);
                }
            }
        }
        if (wg == 1) {
            const int t = tid & 127;
            uint32_t wmax = 0;
#pragma unroll
            for (int k = 0; k < 4; k++) {
                const uint32_t w = ((const uint16_t*)wm)[(256 + k) * 128 + t];
                wmax = max(wmax, w & 0x7fffu);
                *(__half*)(smem + S_W3 + k * 256 + (t & 6) * 32 + (t >> 3) * 4 + (t & 1) * 2) = __float2half_rn(0.5f * __uint_as_float(w << 16));
            }
            bad = wmax >= 0x4300u || !__any_sync(0xffffffffu, wmax >= 0x3B00u);
            __syncwarp();
            if (lane == 0) mbar_arrive(mb + B_W3 * 8);
        } else if (tid < 16) {
            *(uint4*)(scr + G_P + (NULLROW + cta) * 256 + tid * 16) = make_uint4(0xFBFFFBFFu, 0xFBFFFBFFu, 0xFBFFFBFFu, 0xFBFFFBFFu);
        }
        __syncwarp();
        mbar_wait_warp(mb + (B_X + wg) * 8);
        if ((tid & 127) == 0) STAMP(4 + wg);
        const uint32_t ua = sb + S_U + wg * 16384 + ((warp & 3) * 16 + (lane & 15)) * 128 + (((lane >> 4) ^ (lane & 7)) << 4);
        uint32_t xa[8][4];
#pragma unroll
        for (int ks = 0; ks < 8; ks++) ldsm4(xa[ks], (ua ^ ((ks & 3) << 5)) + (ks >> 2) * 8192 + (wg < 2 ? 0 : S_Q - S_U - 32768));
#pragma unroll
        for (int i = 0; i < 32; i++) xa[i >> 2][i & 3] = half_bf2(xa[i >> 2][i & 3]);
        mbar_wait_warp(mb + B_W1 * 8);
        if ((tid & 127) == 0) STAMP(1 + wg);

        float d[32];
        uint32_t v[16];
        gemm_half(d, xa, sb + S_U + 32768);
#pragma unroll
        for (int hh = 0; hh < 5; hh++) {
            gemm_wait(d);
            if (tid == 256) STAMP(40 + 2 * hh);
#pragma unroll
            for (int i = 0; i < 16; i++) v[i] = (hh >> 1) == 1 ? pack_bf(d[2 * i], d[2 * i + 1]) : pack_h(d[2 * i], d[2 * i + 1]);
            auto next = [&]() {
                if (hh == 1 || hh == 3) mbar_wait_warp(mb + (hh == 1 ? B_WT : B_W2) * 8);
                gemm_half(d, xa, sb + (hh < 2 ? S_WB + hh * 16384 : S_RING + (hh - 2) * 16384));
            };
            if (hh != 1) next();
            if (hh == 0) {
                if (wg == 2) { if (lane == 0) mbar_arrive(mb + B_X2FREE * 8); bar_sync(2, 384); }
                else bar_arrive(2, 384);
            } else if (hh == 2) {
                if (lane == 0) mbar_arrive(mb + B_WBFREE * 8);
            }
            if (hh < 4) {
#pragma unroll
                for (int c = 0; c < 4; c++) stsm4((ua ^ (c << 5)) + (hh & 1) * 8192, v[4 * c], v[4 * c + 1], v[4 * c + 2], v[4 * c + 3]);
            }
            if (tid == 256) STAMP(41 + 2 * hh);
            if (hh < 2) {
                fence_async();
                __syncwarp();
                if (lane == 0) tma_store(&tm_p, sb + S_U + wg * 16384 + hh * 8192 + (warp & 3) * 2048, n0 + warp * 16, hh);
                __syncwarp();
            }
            if (hh == 1) {
                next();
                if (lane == 0) { bulk_wait(); mbar_arrive(mb + B_PDONE * 8); }
                __syncwarp();
            }
        }
        uint32_t v1[16];
        gemm_wait(d);
        if (tid == 256) STAMP(50);
#pragma unroll
        for (int i = 0; i < 16; i++) v1[i] = pack_h(d[2 * i], d[2 * i + 1]);
        uint4 wb[8];
        if (wg < 2) {
            uint32_t wmx = 0;
#pragma unroll
            for (int i = 0; i < 8; i++) wb[i] = ldg128((const uint4*)wu + 128 * 16 + tid + i * 256);
#pragma unroll
            for (int i = 0; i < 8; i++) {
                wmx = amax_bf2(amax_bf2(wmx, wb[i].x), amax_bf2(amax_bf2(wb[i].y, wb[i].z), wb[i].w));
                wb[i] = make_uint4(bf2_to_h2(half_bf2(wb[i].x)), bf2_to_h2(half_bf2(wb[i].y)), bf2_to_h2(half_bf2(wb[i].z)), bf2_to_h2(half_bf2(wb[i].w)));
            }
            bad |= !__any_sync(0xffffffffu, mag16(wmx) >= 0x3C00u) || mag16(wmx) >= 0x4780u;
        }
        const uint32_t qs = sb + S_Q + (lane >> 4) * LBO + (warp * 16 + (lane & 15) + 1) * 16;
        mbar_wait_warp(mb + B_EFREE * 8);
#pragma unroll
        for (int c = 0; c < 4; c++) stsm4(qs + (8 + 2 * c) * LBO, v1[4 * c], v1[4 * c + 1], v1[4 * c + 2], v1[4 * c + 3]);
        mbar_wait_warp(mb + B_X2FREE * 8);
#pragma unroll
        for (int c = 0; c < 4; c++) stsm4(qs + 2 * c * LBO, v[4 * c], v[4 * c + 1], v[4 * c + 2], v[4 * c + 3]);
        if (warp == 0) {
            mbar_wait(mb + B_PDONE * 8);
            if (lane == 0) { STAMP(7); grid_arrive(scr, 0, cta); STAMP(52); }
            __syncwarp();
        }
        if (wg < 2) {
            mbar_wait_warp(mb + B_WBFREE * 8);
#pragma unroll
            for (int i = 0; i < 8; i++)
                sts128(sb + S_WB + ((tid >> 3) & 1) * 16384 + ((tid >> 4) + 16 * i) * 128 + (((tid ^ (tid >> 4)) & 7) << 4), wb[i].x, wb[i].y, wb[i].z, wb[i].w);
        }
        if (warp >= 2) {
            mbar_wait_warp(mb + B_SCAN * 8);
            const uint2 mi = lds64(sb + S_MISC + 8);
            const int total = mi.x, t = tid - 64;
            uint32_t pz = 0;
            if (warp < 4) {
                const int T = (total + 32) >> 5, w6 = t >> 3;
                const int b = T / 6, rem = T - b * 6;
                const int L = (b + (w6 < rem)) * 4, pos = (b * w6 + min(w6, rem)) * 32 + (t & 7) * L;
                const uint32_t pa = sb + S_RM + pos * 4;
                auto st = [&](int i) { return lds32(sb + S_ST + ((n0 + i) & 255) * 4); };
                int cnt = st(127) < pa ? 64 : 0;
#pragma unroll
                for (int o = 64; o > 0; o >>= 1) cnt += st(cnt + o - 1) < pa ? o : 0;
                cnt += st(cnt) < pa;
                if (t < 48) sts32(sb + S_TAB + t * 4, pos | (min(cnt, nv + 1) << 12) | (L << 20));
            } else if (warp < 6) {
                if (total >= 0) pz = sb + S_RM + (total + t - 64) * 4;
            } else if (mi.y) {
                const uint32_t i = ((n0 + t - 128) & 255) * 4;
                if (t - 128 < nv && lds32(sb + S_H2 + i) == 0) pz = lds32(sb + S_ST + i);
            }
            if (pz) {
                sts32(pz, ((uint32_t)(NULLROW + cta) << 16) | (t > 64 && t < 128 ? 0x3C00u : 0u));
                sts64(pz * 2 - (sb + (2 * S_RM - S_RE)), 0, 0);
            }
            __syncwarp();
        }
        const uint32_t mx = amax_h2(amax_h2(amax_h2(v[0], v[2]), amax_h2(v[4], v[6])), amax_h2(amax_h2(v[8], v[10]), amax_h2(v[12], v[14])));
        bad |= warp * 16 < nv && !__any_sync(0xffffffffu, mag16(mx) >= 0x2400u);
        if (lane == 0) mbar_arrive(mb + B_JOIN * 8);
        if ((tid & 127) == 0) STAMP(10 + wg);
        asm volatile("setmaxnreg.dec.sync.aligned.u32 80;");
    } else {
        asm volatile("setmaxnreg.dec.sync.aligned.u32 64;");
        const int t = tid - 384, ew = warp - 12;
        const uint32_t tag = (ld_rlx(scr + G_CNT + (cta & 7) * 128) >> 5) + 1;
        const uint32_t glo = (uint32_t)(uintptr_t)scr, ghi = (uint32_t)((uintptr_t)scr >> 32);
        const uint32_t e_s = sb + (2 * S_RM - S_RE), e_g = glo + (2 * G_RM - G_RE);
        const uint32_t ra = sb + S_Q + t * 8, ra3 = sb + S_Q + min(t + 1152, n2 - 1) * 8;
        mbar_wait_warp(mb + B_DST * 8);
        if (t == 0) STAMP(56);
        uint32_t dv[8], ba[8], ps[8];
#pragma unroll
        for (int k = 0; k < 4; k++) { const uint2 v = lds64(k < 3 ? ra + 3072 * k : ra3); dv[2 * k] = v.x * 4; dv[2 * k + 1] = v.y * 4; }
#pragma unroll
        for (int i = 0; i < 8; i++) {
            ba[i] = ((dv[i] * 22076u) >> 24) * 4 + sb;
            if (i >= 6) ba[i] = t + 1152 < n2 ? ba[i] : sb + 135 * 4;
            ps[i] = atoms_inc(ba[i] + S_HIST);
        }
        if (t == 0) STAMP(13);
        bar_sync(5, 384);
        if (ew == 11) {
            int c[5], s = 0;
#pragma unroll
            for (int i = 0; i < 5; i++) { c[i] = lds32(sb + S_HIST + lane * 20 + i * 4); s += c[i]; }
            int inc = s;
#pragma unroll
            for (int o = 1; o < 32; o <<= 1) { const int v = __shfl_up_sync(0xffffffffu, inc, o); if (lane >= o) inc += v; }
            inc -= s;
#pragma unroll
            for (int i = 0; i < 5; i++) {
                sts32(sb + S_OFA + lane * 20 + i * 4, sb + S_RM + inc * 4);
                sts32(sb + S_ENT + lane * 20 + i * 4, inc | (c[i] << 12) | (tag << 24));
                inc += c[i];
            }
            misc[1] = tag;
        }
        bar_sync(5, 384);
        if (ew == 11) {
            fence_async();
            __syncwarp();
            if (lane == 0) bulk_store(scr + G_OFF + cta * OFFS * 4, sb + S_ENT, OFFS * 4);
            __syncwarp();
        }
        if (t == 0) STAMP(32);
#pragma unroll
        for (int i = 0; i < 8; i++) ps[i] = ps[i] * 4 + lds32(ba[i] + S_OFA);
        mbar_wait_warp(mb + B_SRC * 8);
        const uint32_t tg = (tag & 63) << 10;
#pragma unroll
        for (int k = 0; k < 4; k++) { const uint2 v = lds64((k < 3 ? ra + 3072 * k : ra3) + 12288); ba[2 * k] = v.x; ba[2 * k + 1] = v.y; }
#pragma unroll
        for (int i = 0; i < 8; i++) sts32(ps[i], (dv[i] & 0x3FCu) | (ba[i] * 65536u + tg));
        fence_async();
        __syncwarp();
        if (lane == 0) mbar_arrive(mb + B_DSFREE * 8);
        mbar_wait_warp(mb + B_DSFREE * 8);
        if (t == 0) { STAMP(58); bulk_store(scr + G_RM + cta * CHP * 4, sb + S_RM, n2 * 8); }
        __syncwarp();
        while ((uint32_t)clock() - t_start < sched.t_off) {}
        uint32_t m[12], ga[12];
        {
            const int c = ew * 11 + min(lane, 10);
            uint32_t ent;
            int it = 0;
#pragma unroll 1
            do { ent = ld_rlx(scr + G_OFF + (c * OFFS + cta) * 4); } while (__any_sync(0xffffffffu, ((ent >> 24) ^ tag) & 0xFF) && ++it < SPIN);
            if (it >= SPIN) { bad = true; ent = 0; }
            if (t == 0) STAMP(16);
            const uint32_t beg = glo + G_RM + (c * CHP + (ent & 0xFFF)) * 4, end = beg + ((ent >> 10) & 0x3FFC);
            sts64(sb + S_OFA + c * 8, beg, end);
            uint32_t more = __ballot_sync(0xffffffffu, end - beg > 128) & 0x7FFu, used = 0;
            ga[11] = 0;
#pragma unroll 1
            while (more) {
                const uint2 v = lds64(sb + S_OFA + (ew * 11 + __ffs(more) - 1) * 8);
                if (lane * 4 >= used) ga[11] = v.x + 128 + lane * 4 - used;
                used += v.y - v.x - 128;
                more &= more - 1;
            }
            bad |= used > 128;
            mbar_wait_warp(mb + B_E * 8);
            if (t == 0) STAMP(57);
            uint4 u[4];
#pragma unroll
            for (int k = 0; k < 4; k++) u[k] = lds128((k < 3 ? ra + 3072 * k : ra3) * 2 - (sb + (2 * S_Q - S_RAWE)));
#pragma unroll
            for (int k = 0; k < 4; k++) {
                sts64(ps[2 * k] * 2 - e_s, (bf2_to_h2(u[k].x) & ~3u) | (tag & 3), bf2_to_h2(u[k].y));
                sts64(ps[2 * k + 1] * 2 - e_s, (bf2_to_h2(u[k].z) & ~3u) | (tag & 3), bf2_to_h2(u[k].w));
            }
            if (t == 0) STAMP(33);
            fence_async();
            __syncwarp();
            if (lane == 0) mbar_arrive(mb + B_EFREE * 8);
            if (ew == 0) {
                mbar_wait(mb + B_EFREE * 8);
                if (lane == 0) { STAMP(14); bulk_store(scr + G_RE + cta * CHP * 8, sb + S_RE, n2 * 16); }
                __syncwarp();
            }
            while ((uint32_t)clock() - t_start < sched.t_rec) {}
            const uint32_t idle = (((n0 + 192 + lane) & 255) << 2) | tg;
            bool again;
            it = 0;
#pragma unroll 1
            do {
                uint32_t df = 0;
#pragma unroll
                for (int r = 0; r < 12; r++) {
                    uint32_t lhs = lane * 4, rhs = used;
                    if (r < 11) { const uint2 v = lds64(sb + S_OFA + (ew * 11 + r) * 8); lhs = ga[r] = v.x + lane * 4; rhs = v.y; }
                    m[r] = idle;
                    asm volatile("{.reg .pred p; .reg .b64 a; setp.lt.u32 p,%3,%4; mov.b64 a,{%1,%2}; @p ld.relaxed.gpu.global.u32 %0,[a];}"
                                 : "+r"(m[r]) : "r"(ga[r]), "r"(ghi), "r"(lhs), "r"(rhs) : "memory");
                }
#pragma unroll
                for (int r = 0; r < 12; r++) df |= m[r] ^ tg;
                again = __any_sync(0xffffffffu, df & 0xFC00u);
            } while (again && ++it < SPIN);
            bad |= again;
        }
        if (t == 0) STAMP(35);
        uint32_t rk[12];
#pragma unroll
        for (int r = 0; r < 12; r++) rk[r] = atoms_inc(sb + S_H2 + (m[r] & 0x3FCu));
        if (t == 0) STAMP(17);
        bar_sync(5, 384);
        if (ew == 0) {
            if (lane == 0) {
                asm volatile("cp.async.bulk.commit_group;" ::: "memory");
                asm volatile("cp.async.bulk.wait_group.read 0;" ::: "memory");
            }
            __syncwarp();
        } else if (ew == 11) {
            int c[6], s = 0, cm = 0;
            bool z = false;
#pragma unroll
            for (int i = 0; i < 6; i++) {
                c[i] = lds32(sb + S_H2 + ((n0 + lane * 6 + i) & 255) * 4);
                if (lane * 6 + i < nv) { z |= c[i] == 0; c[i] = max(c[i], 1); }
                s += c[i];
                cm = max(cm, c[i]);
            }
            int inc = s;
#pragma unroll
            for (int o = 1; o < 32; o <<= 1) { const int v = __shfl_up_sync(0xffffffffu, inc, o); if (lane >= o) inc += v; }
            const int total = __shfl_sync(0xffffffffu, inc, 31);
            const bool over = __any_sync(0xffffffffu, cm > 256) || total + 64 > RCAP;
            inc -= s;
#pragma unroll
            for (int i = 0; i < 6; i++) { sts32(sb + S_ST + ((n0 + lane * 6 + i) & 255) * 4, over ? 0 : sb + S_RM + inc * 4); inc += c[i]; }
            sts32(sb + S_ST + ((n0 + 192 + lane) & 255) * 4, 0);
            sts32(sb + S_ST + ((n0 + 224 + lane) & 255) * 4, 0);
            sts64(sb + S_MISC + 8, over ? -1 : total, __any_sync(0xffffffffu, z));
            bad |= over;
        }
        bar_sync(5, 384);
        if (t == 0) { mbar_arrive(mb + B_SCAN * 8); STAMP(37); }
#pragma unroll
        for (int r = 0; r < 12; r++) {
            uint32_t keep;
            asm("set.ne.f16x2.f16x2 %0,%1,%2;" : "=r"(keep) : "r"(rk[r]), "r"(0));
            rk[r] = rk[r] * 4 + lds32(sb + S_ST + (m[r] & 0x3FCu));
            m[r] = (m[r] & 0xFFFF0000u) | keep;
        }
#pragma unroll
        for (int r = 0; r < 12; r++)
            asm volatile("{.reg .pred p; setp.ge.u32 p,%0,%2; @p st.shared.u32 [%0],%1;}" ::"r"(rk[r]), "r"(m[r]), "n"(S_RM) : "memory");
        if (t == 0) STAMP(60);
        while ((uint32_t)clock() - t_start < sched.t_e) {}
        {
            uint2 ee[12];
            bool again;
            int it = 0;
#pragma unroll 1
            do {
                uint32_t df = 0;
#pragma unroll
                for (int r = 0; r < 12; r++) {
                    const uint32_t a = r < 11 ? lds32(sb + S_OFA + (ew * 11 + r) * 8) * 2 + (lane * 8 - e_g) : ga[r] * 2 - e_g;
                    ee[r].x = tag;
                    asm volatile("{.reg .pred p; .reg .b64 a; setp.ge.u32 p,%4,%5; mov.b64 a,{%2,%3}; @p ld.relaxed.gpu.global.v2.u32 {%0,%1},[a];}"
                                 : "+r"(ee[r].x), "=r"(ee[r].y) : "r"(a), "r"(ghi), "r"(rk[r]), "r"(S_RM - 4 - (it & 1)) : "memory");
                }
#pragma unroll
                for (int r = 0; r < 12; r++) df |= ee[r].x ^ tag;
                again = __any_sync(0xffffffffu, df & 3u);
            } while (again && ++it < SPIN);
            bad |= again;
            if (t == 0) STAMP(62);
#pragma unroll
            for (int r = 0; r < 12; r++)
                asm volatile("{.reg .pred p; setp.ge.u32 p,%3,%4; @p st.shared.v2.u32 [%0],{%1,%2};}"
                             ::"r"(rk[r] * 2 - e_s), "r"(ee[r].x & ~3u), "r"(ee[r].y), "r"(rk[r]), "n"(S_RM - 1) : "memory");
        }
        __syncwarp();
        if (lane == 0) mbar_arrive(mb + B_JOIN * 8);
        if (t == 0) STAMP(18);
        asm volatile("setmaxnreg.inc.sync.aligned.u32 80;");
    }

    const int l16 = lane & 15;
    uint32_t qa, qv[4], acc[4] = {0, 0, 0, 0}, w[4][4];
    mbar_wait_warp(mb + B_W3 * 8);
#pragma unroll
    for (int k = 0; k < 16; k++) w[k >> 2][k & 3] = lds32(sb + S_W3 + k * 64 + l16 * 4);
    const uint32_t zero = opaque(threadIdx.x >> 20);
    const uint32_t pLo = opaque((uint32_t)(uintptr_t)scr + l16 * 16), pHi = opaque((uint32_t)((uintptr_t)scr >> 32) + (threadIdx.x >> 21));
    const uint32_t trash = opaque(sb + S_Q + l16 * LBO + 199 * 16);
    if (warp == 0) {
        bad |= grid_wait(scr, 0, misc[1], lane);
        if (lane == 0) { mbar_arrive(mb + B_GO * 8); STAMP(19); }
    }
    mbar_wait_warp(mb + B_JOIN * 8);
    if (tid == 0) STAMP(38);
    const uint32_t tab = lds32(sb + S_TAB + (tid >> 4) * 4);
    qa = sb + S_Q + l16 * LBO + ((tab >> 8) & 0xFF0u);
    { const uint4 v = lds128(qa); qv[0] = v.x; qv[1] = v.y; qv[2] = v.z; qv[3] = v.w; }
    uint32_t mp = sb + S_RM + (tab & 0xFFFu) * 4, ep = sb + S_RE + (tab & 0xFFFu) * 8;
    const uint4 mfirst = lds128(mp);
    const uint32_t qa0 = qa;
    if (tid == 0) STAMP(39);
    uint32_t e[2][4], p[2][2][4], h[2][4] = {}, cu[2][2] = {{mfirst.x, mfirst.y}, {mfirst.z, mfirst.w}}, nx[2];
    auto gather = [&](uint32_t(&d)[4], uint32_t m, uint32_t dep) {
        uint32_t hi;
        uint64_t a;
        asm("lop3.b32 %0,%1,%2,%3,0xF8;" : "=r"(hi) : "r"(pHi), "r"(dep), "r"(zero));
        asm("mov.b64 %0,{%1,%2};" : "=l"(a) : "r"(prmt(m, pLo, 0x7324)), "r"(hi));
        asm volatile("ld.relaxed.gpu.global.v4.u32 {%0,%1,%2,%3},[%4];" : "=r"(d[0]), "=r"(d[1]), "=r"(d[2]), "=r"(d[3]) : "l"(a) : "memory");
    };
    auto lde = [&](uint32_t(&d)[4], uint32_t a) { const uint4 v = lds128(a); d[0] = v.x; d[1] = v.y; d[2] = v.z; d[3] = v.w; };
    auto stage_a = [&](uint32_t(&o)[4], const uint32_t(&pr)[4], uint32_t e01, uint32_t e23) {
        const __half2 e0 = __low2half2(H2(e01)), e1 = __high2half2(H2(e01)), e2 = __low2half2(H2(e23)), e3 = __high2half2(H2(e23));
#pragma unroll
        for (int j = 0; j < 4; j++)
            o[j] = U32(__hfma2(e3, H2(w[3][j]), __hfma2(e2, H2(w[2][j]), __hfma2(e1, H2(w[1][j]), __hfma2(e0, H2(w[0][j]), H2(pr[j]))))));
    };
    auto blk = [&](auto S, auto I) {
        constexpr int s = S.value, i = I.value;
        const bool first = (cu[s][i] & 0xFFFFu) == 0;
        if (__any_sync(0xffffffffu, first)) {
            sts64(trash, h[i][0] ^ h[i][1], h[i][2] ^ h[i][3]);
            if (first) {
                qa += 16;
                lde(qv, qa);
                sts128(qa, acc[0], acc[1], acc[2], acc[3]);
                acc[0] = acc[1] = acc[2] = acc[3] = 0;
            }
            __syncwarp();
        }
        if (i == 0) {
            lde(e[s ^ 1], ep + (s + 1) * 16);
            const uint2 v = lds64(mp + (s + 2) * 8);
            nx[0] = v.x; nx[1] = v.y;
            stage_a(h[1], p[s][1], e[s][2], e[s][3]);
        } else {
            gather(p[s][0], nx[0], p[s ^ 1][1][0]);
            gather(p[s][1], nx[1], p[s ^ 1][1][0]);
            cu[s][0] = nx[0]; cu[s][1] = nx[1];
            stage_a(h[0], p[s ^ 1][0], e[s ^ 1][0], e[s ^ 1][1]);
        }
#pragma unroll
        for (int j = 0; j < 4; j++) {
            const __half2 t = __hadd2(H2(h[i][j]), H2(qv[j]));
            acc[j] = U32(__hadd2(H2(acc[j]), __hfma2(t, H2(tanh_h2(U32(t))), t)));
        }
    };
    using C0 = std::integral_constant<int, 0>;
    using C1 = std::integral_constant<int, 1>;
    lde(e[0], ep);
    mbar_wait_warp(mb + B_GO * 8);
#pragma unroll
    for (int i = 0; i < 4; i++) gather(p[i >> 1][i & 1], cu[i >> 1][i & 1], zero);
    const int L = uni(__syncthreads_or(bad) ? -1 : (int)(tab >> 20));
    if (L < 0) {
        generic_path(smem, x, ea, src, dst, wm, wu, out);
        return;
    }
    if (tid == 0) STAMP(20);
    stage_a(h[0], p[0][0], e[0][0], e[0][1]);
#pragma unroll 1
    for (int it = 0; it < L; it += 4) {
        blk(C0{}, C0{}); blk(C0{}, C1{}); blk(C1{}, C0{}); blk(C1{}, C1{});
        mp += 16; ep += 32;
    }
    if (lane == 0 && (warp & 3) == 0) STAMP(21 + (warp >> 2));

    const int tile = warp >> 3, half = (warp >> 2) & 1, g = lane >> 2;
    const int r0 = tile * 64 + (warp & 3) * 16;
    float d[32];
    const uint32_t ub = sb + S_U + (warp >> 2) * 8192 + (warp & 3) * 2048;
    const uint32_t ua = ub + (lane & 15) * 128 + (((lane >> 4) ^ (lane & 7)) << 4);
#pragma unroll
    for (int c = 0; c < 4; c++) {
        uint32_t u[4];
        ldsm4(u, ua ^ (c << 5));
#pragma unroll
        for (int i = 0; i < 4; i++) { d[8 * c + 2 * i] = __uint_as_float(u[i] << 16); d[8 * c + 2 * i + 1] = __uint_as_float(u[i] & 0xffff0000u); }
    }
    const bool live = qa < sb + S_Q + l16 * LBO + (nv + 1) * 16;
    const bool shared_target = __syncthreads_or(live && qa == qa0);
    if (tid == 0) STAMP(53);
    if (shared_target) {
#pragma unroll
        for (int j = 0; j < 4; j++) asm volatile("red.shared.add.noftz.f16x2 [%0],%1;" ::"r"(qa + 16 + j * 4), "r"(acc[j]) : "memory");
    } else if (live) {
        const uint4 v = lds128(qa + 16);
        sts128(qa + 16, U32(__hadd2(H2(v.x), H2(acc[0]))), U32(__hadd2(H2(v.y), H2(acc[1]))), U32(__hadd2(H2(v.z), H2(acc[2]))), U32(__hadd2(H2(v.w), H2(acc[3]))));
    }
    if (tid == 0) STAMP(54);
    fence_async();
    if (tid == 0) STAMP(55);
    __syncthreads();
    if (tid == 0) STAMP(27);
    {
        const uint64_t da = ((uint64_t)8 << 32) | ((uint64_t)(LBO >> 4) << 16) | (uint64_t)(((sb + S_Q + (tile * 64 + 2) * 16) & 0x3FFFF) >> 4);
        const uint64_t db = ((uint64_t)1 << 62) | ((uint64_t)64 << 32) | ((uint64_t)1 << 16) | (uint64_t)(((sb + S_WB + half * 16384) & 0x3FFFF) >> 4);
        if (warp >= 4) bar_sync(7 + (warp >> 2), 256);
        asm volatile("wgmma.fence.sync.aligned;" ::: "memory");
#pragma unroll
        for (int ks = 0; ks < 8; ks++)
            asm volatile(
                "wgmma.mma_async.sync.aligned.m64n64k16.f32.f16.f16 "
                "{%0,%1,%2,%3,%4,%5,%6,%7,%8,%9,%10,%11,%12,%13,%14,%15,%16,%17,%18,%19,%20,%21,%22,%23,%24,%25,%26,%27,%28,%29,%30,%31},"
                "%32,%33,1,1,1,0,1;"
                : "+f"(d[0]), "+f"(d[1]), "+f"(d[2]), "+f"(d[3]), "+f"(d[4]), "+f"(d[5]), "+f"(d[6]), "+f"(d[7]),
                  "+f"(d[8]), "+f"(d[9]), "+f"(d[10]), "+f"(d[11]), "+f"(d[12]), "+f"(d[13]), "+f"(d[14]), "+f"(d[15]),
                  "+f"(d[16]), "+f"(d[17]), "+f"(d[18]), "+f"(d[19]), "+f"(d[20]), "+f"(d[21]), "+f"(d[22]), "+f"(d[23]),
                  "+f"(d[24]), "+f"(d[25]), "+f"(d[26]), "+f"(d[27]), "+f"(d[28]), "+f"(d[29]), "+f"(d[30]), "+f"(d[31])
                : "l"(da + ks * (2 * LBO >> 4)), "l"(db + ks * 128));
        asm volatile("wgmma.commit_group.sync.aligned;" ::: "memory");
        if (warp < 20) bar_arrive(8 + (warp >> 2), 256);
        asm volatile("wgmma.wait_group.sync.aligned 0;" ::: "memory");
#pragma unroll
        for (int i = 0; i < 32; i++) asm volatile("" : "+f"(d[i])::"memory");
    }
    if (tid == 0) STAMP(28);
    if (tid == 256) STAMP(8);
    if (tid == 640) STAMP(9);
    bad = (r0 + g < nv && !(fabsf(d[0]) < 3e38f)) || (r0 + g + 8 < nv && !(fabsf(d[2]) < 3e38f));
#pragma unroll
    for (int c = 0; c < 4; c++) {
        uint32_t o[4];
#pragma unroll
        for (int i = 0; i < 4; i++) {
            const float a = d[8 * c + 2 * i], b = d[8 * c + 2 * i + 1];
            o[i] = pack_bf(fmaf(a, tanh_f(a), a), fmaf(b, tanh_f(b), b));
        }
        stsm4(ua ^ (c << 5), o[0], o[1], o[2], o[3]);
    }
    __syncwarp();
    {
        uint4* op = (uint4*)out + (n0 + r0 + (lane >> 3)) * 16 + half * 8 + (lane & 7);
#pragma unroll
        for (int k = 0; k < 4; k++) {
            const int row = k * 4 + (lane >> 3);
            const uint4 v = lds128(ub + row * 128 + (((lane ^ row) & 7) << 4));
            if (r0 + row < nv) op[k * 64] = v;
        }
    }
    if (tid == 0) STAMP(29);
    if (tid == 256) STAMP(36);
    if (tid == 640) STAMP(31);
    if (__syncthreads_or(bad)) generic_path(smem, x, ea, src, dst, wm, wu, out);
    if (tid == 0) { STAMP(30); GSTAMP(1); }
}

}

typedef CUresult (*EncodeFn)(CUtensorMap*, CUtensorMapDataType, cuuint32_t, void*, const cuuint64_t*, const cuuint64_t*, const cuuint32_t*,
                             const cuuint32_t*, CUtensorMapInterleave, CUtensorMapSwizzle, CUtensorMapL2promotion, CUtensorMapFloatOOBfill);

static void encode_rows(EncodeFn fn, CUtensorMap* tm, void* p, int rows, int box_rows, int box_halves) {
    const cuuint64_t dims[3] = {64, (cuuint64_t)rows, 2};
    const cuuint64_t strides[2] = {256, 128};
    const cuuint32_t box[3] = {64, (cuuint32_t)box_rows, (cuuint32_t)box_halves}, es[3] = {1, 1, 1};
    fn(tm, CU_TENSOR_MAP_DATA_TYPE_BFLOAT16, 3, p, dims, strides, box, es, CU_TENSOR_MAP_INTERLEAVE_NONE, CU_TENSOR_MAP_SWIZZLE_128B,
       CU_TENSOR_MAP_L2_PROMOTION_L2_256B, CU_TENSOR_MAP_FLOAT_OOB_FILL_NONE);
}

extern "C" void kernel_launch(void* const* d_in, const int* in_sizes, int n_in, void* d_out, int out_size) {
    (void)in_sizes; (void)n_in; (void)out_size;
    static EncodeFn encode = nullptr;
    static void* pbase = nullptr;
    if (!encode) {
        cudaFuncSetAttribute(mpnn_kernel, cudaFuncAttributeMaxDynamicSharedMemorySize, S_TOTAL);
        void* fn = nullptr;
        cudaDriverEntryPointQueryResult qr;
        cudaGetDriverEntryPoint("cuTensorMapEncodeTiled", &fn, cudaEnableDefault, &qr);
        encode = (EncodeFn)fn;
        cudaGetSymbolAddress(&pbase, g_scratch);
        pbase = (void*)(((uintptr_t)pbase + 0xFFFFFFull) & ~(uintptr_t)0xFFFFFFull);
    }
    Sched sched;
    {
        const uint32_t ev[][2] = {{500, EV_SRC}, {500, EV_W1}, {1500, EV_X}, {1500, EV_WT}, {2900, EV_E}, {2900, EV_W2}, {3900, EV_E + 1}, {4900, EV_X + 1}, {6300, EV_X + 2}, {0, EV_END}};
        sched.t_off = 4800; sched.t_rec = 7000; sched.t_e = 0;
        for (int i = 0; i < 32; i++) sched.ev[i] = i < (int)(sizeof(ev) / sizeof(ev[0])) ? ev[i][0] << 8 | ev[i][1] : EV_END;
    }
    CUtensorMap tm_msg, tm_upd, tm_x, tm_p;
    encode_rows(encode, &tm_msg, d_in[4], 256, 128, 1);
    encode_rows(encode, &tm_upd, d_in[5], 256, 128, 1);
    encode_rows(encode, &tm_x, d_in[0], NN, 64, 2);
    encode_rows(encode, &tm_p, pbase, NULLROW, 16, 1);
    mpnn_kernel<<<NCTA, NTHR, S_TOTAL, cudaStreamPerThread>>>(
        (const __nv_bfloat16*)d_in[0], (const __nv_bfloat16*)d_in[1], (const int*)d_in[2], (const int*)d_in[3],
        (const __nv_bfloat16*)d_in[4], (const __nv_bfloat16*)d_in[5], (__nv_bfloat16*)d_out, (char*)pbase, sched, tm_msg, tm_upd, tm_x, tm_p);
}
```

```cpp
#include <cuda.h>
#include <cuda_runtime.h>
#include <cuda_bf16.h>
#include <cuda_fp16.h>
#include <stdint.h>
#include <type_traits>

namespace {

constexpr int NN = 25000, NE = 400000;
constexpr int NCTA = 132, NT = 190;
constexpr uint32_t OWN = 22145;
constexpr int CH = 3032;
constexpr int CHP = 3040;
constexpr int OFFS = 136;
constexpr int RCAP = 3520;
constexpr int NTHR = 768;
constexpr int SPIN = 1 << 14;
constexpr int NULLROW = 25088;
constexpr int LBO = 3216;
constexpr uint64_t WPERM = 0xFEDCBA9876543210ull;
constexpr uint32_t T_SRC = 1000, T_W1 = 1200, T_X0 = 1700, T_WT = 2200, T_W2 = 3000, T_X1 = 3400, T_X2 = 5200, T_E0 = 6700, T_E1 = 7400;
constexpr uint32_t T_OFF = 5200, T_REC = 6000, T_ER = 13250;

constexpr int S_U = 0;
constexpr int S_WX = 49152;
constexpr int S_WB = S_WX + 49152;
constexpr int S_Q = S_WB + 32768;
constexpr int S_RAWS = S_Q + 16384, S_RAWE = S_RAWS + CH * 4;
constexpr int S_RE = S_RAWE + CH * 8;
constexpr int S_RM = S_RE + RCAP * 8;
constexpr int S_W3 = S_RM + RCAP * 4;
constexpr int S_HIST = S_W3 + 1024;
constexpr int S_H2 = S_HIST + 640;
constexpr int S_MISC = S_H2 + 1024;
constexpr int S_ENT = S_MISC + 64;
constexpr int S_OFA = S_ENT + 640;
constexpr int S_ST = S_OFA + 1056;
constexpr int S_TAB = S_ST + 1024;
constexpr int S_MBAR = S_TAB + 192;
constexpr int S_TOTAL = S_MBAR + 256;
static_assert(S_TOTAL <= 232448, "smem");
static_assert(S_RE >= S_Q + 16 * LBO && S_RAWE % 16 == 0 && S_RE % 16 == 0, "layout");
enum { B_DST, B_SRC, B_E0, B_E, B_W1, B_WT, B_W2, B_X, B_GO = B_X + 3, B_SCAN, B_ESENT, B_WB, B_X2FREE, B_DSFREE, B_EFREE, B_PDONE, B_JOIN, B_READY, B_NUM };

constexpr uint32_t G_P = 0;
constexpr uint32_t G_RM = 0x630000;
constexpr uint32_t G_RE = 0x7C0000;
constexpr uint32_t G_OFF = 0xAD0000;
constexpr uint32_t G_WB = 0xB00000;
constexpr uint32_t G_CNT = 0xAF8000;
__device__ uint4 g_scratch[(32u << 20) / 16];

__device__ __forceinline__ int first_node(int cta) { return min((int)((((uint32_t)cta << 22) + OWN - 1) / OWN), NN); }
__device__ __forceinline__ uint32_t smem_u32(const void* p) { return (uint32_t)__cvta_generic_to_shared(p); }
__device__ __forceinline__ int uni(int v) { return __shfl_sync(0xffffffffu, v, 0); }
__device__ __forceinline__ uint32_t opaque(uint32_t v) { return __shfl_sync(0xffffffffu, v, threadIdx.x & 31); }
__device__ __forceinline__ int fresh_tid() { int v; asm volatile("mov.u32 %0,%%tid.x;" : "=r"(v)); return v; }
__device__ __forceinline__ int fresh_cta() { int v; asm volatile("mov.u32 %0,%%ctaid.x;" : "=r"(v)); return v; }
__device__ __forceinline__ bool elect() {
    uint32_t r; asm volatile("{.reg .pred p; elect.sync _|p,0xffffffff; selp.u32 %0,1,0,p;}" : "=r"(r)); return r != 0;
}
__device__ __forceinline__ void bar_sync(int id, int n) { asm volatile("bar.sync %0,%1;" ::"r"(id), "r"(n) : "memory"); }
__device__ __forceinline__ uint32_t prmt(uint32_t a, uint32_t b, uint32_t c) {
    uint32_t r; asm("prmt.b32 %0,%1,%2,%3;" : "=r"(r) : "r"(a), "r"(b), "r"(c)); return r;
}
__device__ __forceinline__ uint32_t pack_bf(float lo, float hi) {
    uint32_t r; asm("cvt.rn.bf16x2.f32 %0,%1,%2;" : "=r"(r) : "f"(hi), "f"(lo)); return r;
}
__device__ __forceinline__ uint32_t pack_h(float lo, float hi) {
    uint32_t r; asm("cvt.rn.f16x2.f32 %0,%1,%2;" : "=r"(r) : "f"(hi), "f"(lo)); return r;
}
__device__ __forceinline__ uint32_t bf2_to_h2(uint32_t w) {
    return pack_h(__uint_as_float(w << 16), __uint_as_float(w & 0xffff0000u));
}
__device__ __forceinline__ uint32_t put_tag(uint32_t v, uint32_t tag) {
    uint32_t r; asm("lop3.b32 %0,%1,3,%2,0xB8;" : "=r"(r) : "r"(v), "r"(tag)); return r;
}
__device__ __forceinline__ uint32_t amax_h2(uint32_t a, uint32_t b) {
    uint32_t r; asm("max.NaN.xorsign.abs.f16x2 %0,%1,%2;" : "=r"(r) : "r"(a), "r"(b)); return r;
}
__device__ __forceinline__ uint32_t amax_bf2(uint32_t a, uint32_t b) {
    uint32_t r; asm("max.NaN.xorsign.abs.bf16x2 %0,%1,%2;" : "=r"(r) : "r"(a), "r"(b)); return r;
}
__device__ __forceinline__ uint32_t mag16(uint32_t w) { return max(w & 0x7fffu, (w >> 16) & 0x7fffu); }
__device__ __forceinline__ uint32_t half_bf2(uint32_t a) {
    uint32_t r; asm("mul.rn.bf16x2 %0,%1,%2;" : "=r"(r) : "r"(a), "r"(0x3F003F00u)); return r;
}
__device__ __forceinline__ float tanh_f(float x) { float y; asm("tanh.approx.f32 %0,%1;" : "=f"(y) : "f"(x)); return y; }
__device__ __forceinline__ void stsm4(uint32_t a, uint32_t r0, uint32_t r1, uint32_t r2, uint32_t r3) {
    asm volatile("stmatrix.sync.aligned.m8n8.x4.shared.b16 [%0],{%1,%2,%3,%4};" ::"r"(a), "r"(r0), "r"(r1), "r"(r2), "r"(r3) : "memory");
}
__device__ __forceinline__ uint4 lds128(uint32_t a) {
    uint4 v; asm volatile("ld.shared.v4.u32 {%0,%1,%2,%3},[%4];" : "=r"(v.x), "=r"(v.y), "=r"(v.z), "=r"(v.w) : "r"(a) : "memory"); return v;
}
__device__ __forceinline__ void sts128(uint32_t a, uint32_t x, uint32_t y, uint32_t z, uint32_t w) {
    asm volatile("st.shared.v4.u32 [%0],{%1,%2,%3,%4};" ::"r"(a), "r"(x), "r"(y), "r"(z), "r"(w) : "memory");
}
__device__ __forceinline__ uint32_t ld_rlx(const void* p) {
    uint32_t v; asm volatile("ld.relaxed.gpu.global.u32 %0,[%1];" : "=r"(v) : "l"(p) : "memory"); return v;
}

__device__ __forceinline__ __half2 H2(uint32_t v) { return *(__half2*)&v; }
__device__ __forceinline__ uint32_t U32(__half2 v) { return *(uint32_t*)&v; }
__device__ __forceinline__ uint32_t tanh_h2(uint32_t h) { uint32_t t; asm("tanh.approx.f16x2 %0,%1;" : "=r"(t) : "r"(h)); return t; }
__device__ __forceinline__ void bar_arrive(int id, int n) { asm volatile("bar.arrive %0,%1;" ::"r"(id), "r"(n) : "memory"); }
__device__ __forceinline__ void fence_async() { asm volatile("fence.proxy.async.shared::cta;" ::: "memory"); }
__device__ __forceinline__ void bulk_store(void* g, uint32_t s, int bytes) {
    asm volatile("cp.async.bulk.global.shared::cta.bulk_group [%0],[%1],%2;" ::"l"(g), "r"(s), "r"(bytes) : "memory");
}
__device__ __forceinline__ void bulk_commit() { asm volatile("cp.async.bulk.commit_group;" ::: "memory"); }
__device__ __forceinline__ void bulk_wait() {
    asm volatile("cp.async.bulk.commit_group;" ::: "memory");
    asm volatile("cp.async.bulk.wait_group 0;" ::: "memory");
}
__device__ __forceinline__ void gemm_half(float (&d)[32], const uint32_t (&xa)[8][4], uint32_t bsm) {
    const uint64_t desc = ((uint64_t)1 << 62) | ((uint64_t)64 << 32) | ((uint64_t)1 << 16) | (uint64_t)((bsm & 0x3FFFF) >> 4);
    asm volatile("wgmma.fence.sync.aligned;" ::: "memory");
#pragma unroll
    for (int ks = 0; ks < 8; ks++) {
        asm volatile(
            "{.reg .pred p; setp.ne.b32 p,%37,0;\n"
            "wgmma.mma_async.sync.aligned.m64n64k16.f32.bf16.bf16 "
            "{%0,%1,%2,%3,%4,%5,%6,%7,%8,%9,%10,%11,%12,%13,%14,%15,%16,%17,%18,%19,%20,%21,%22,%23,%24,%25,%26,%27,%28,%29,%30,%31},"
            "{%32,%33,%34,%35},%36,p,1,1,1;}"
            : "+f"(d[0]), "+f"(d[1]), "+f"(d[2]), "+f"(d[3]), "+f"(d[4]), "+f"(d[5]), "+f"(d[6]), "+f"(d[7]),
              "+f"(d[8]), "+f"(d[9]), "+f"(d[10]), "+f"(d[11]), "+f"(d[12]), "+f"(d[13]), "+f"(d[14]), "+f"(d[15]),
              "+f"(d[16]), "+f"(d[17]), "+f"(d[18]), "+f"(d[19]), "+f"(d[20]), "+f"(d[21]), "+f"(d[22]), "+f"(d[23]),
              "+f"(d[24]), "+f"(d[25]), "+f"(d[26]), "+f"(d[27]), "+f"(d[28]), "+f"(d[29]), "+f"(d[30]), "+f"(d[31])
            : "r"(xa[ks][0]), "r"(xa[ks][1]), "r"(xa[ks][2]), "r"(xa[ks][3]), "l"(desc + ks * 128), "r"(ks));
    }
    asm volatile("wgmma.commit_group.sync.aligned;" ::: "memory");
}
__device__ __forceinline__ void gemm_wait(float (&d)[32]) {
    asm volatile("wgmma.wait_group.sync.aligned 0;" ::: "memory");
#pragma unroll
    for (int i = 0; i < 32; i++) asm volatile("" : "+f"(d[i])::"memory");
}
__device__ __forceinline__ void fence_acquire() { asm volatile("fence.acquire.gpu;" ::: "memory"); }

__device__ __forceinline__ void mbar_wait(uint32_t bar) {
    uint32_t ok = 0, n = bar;
#pragma unroll 1
    while (!ok && --n)
        asm volatile("{.reg .pred p; mbarrier.try_wait.parity.shared::cta.b64 p,[%1],0; selp.u32 %0,1,0,p;}" : "=r"(ok) : "r"(bar) : "memory");
}
__device__ __forceinline__ void mbar_wait_warp(uint32_t bar) { mbar_wait(bar); __syncwarp(); }
__device__ __forceinline__ void grid_arrive(char* scr, int cta) {
    asm volatile("fence.release.gpu;" ::: "memory");
    asm volatile("red.relaxed.gpu.global.add.u32 [%0],%1;" ::"l"(scr + G_CNT + (cta & 7) * 128), "r"(cta < 8 ? (cta < 4 ? 16u : 17u) : 1u) : "memory");
}
__device__ __forceinline__ bool grid_wait(const char* scr, uint32_t tag, int lane) {
    int it = 0;
#pragma unroll 1
    while (__any_sync(0xffffffffu, (int)(ld_rlx(scr + G_CNT + (lane & 7) * 128) - (tag << 5)) < 0) && ++it < SPIN) {}
    fence_acquire();
    return it >= SPIN;
}
__device__ __forceinline__ void mbar_expect(uint32_t bar, int bytes) {
    asm volatile("mbarrier.arrive.expect_tx.shared::cta.b64 _,[%0],%1;" ::"r"(bar), "r"(bytes) : "memory");
}
__device__ __forceinline__ void bulk_load(uint32_t s, const void* g, int bytes, uint32_t bar) {
    asm volatile("cp.async.bulk.shared::cluster.global.mbarrier::complete_tx::bytes [%0],[%1],%2,[%3];" ::"r"(s), "l"(g), "r"(bytes), "r"(bar) : "memory");
}
__device__ __forceinline__ void mbar_arrive(uint32_t bar) { asm volatile("mbarrier.arrive.shared::cta.b64 _,[%0];" ::"r"(bar) : "memory"); }
__device__ __forceinline__ void tma_load(uint32_t s, const CUtensorMap* tm, int row, int half, uint32_t bar) {
    asm volatile("cp.async.bulk.tensor.3d.shared::cluster.global.mbarrier::complete_tx::bytes [%0],[%1,{%5,%3,%4}],[%2];"
                 ::"r"(s), "l"(tm), "r"(bar), "r"(row), "r"(half), "r"(0) : "memory");
}
__device__ __forceinline__ void tma_store(const CUtensorMap* tm, uint32_t s, int row, int half) {
    asm volatile("cp.async.bulk.tensor.3d.global.shared::cta.bulk_group [%0,{%4,%2,%3}],[%1];" ::"l"(tm), "r"(s), "r"(row), "r"(half), "r"(0) : "memory");
}
__device__ __forceinline__ void ldsm4(uint32_t (&r)[4], uint32_t a) {
    asm volatile("ldmatrix.sync.aligned.m8n8.x4.shared.b16 {%0,%1,%2,%3},[%4];"
                 : "=r"(r[0]), "=r"(r[1]), "=r"(r[2]), "=r"(r[3]) : "r"(a) : "memory");
}
__device__ __forceinline__ uint4 ldg128(const void* p) {
    uint4 v; asm volatile("ld.global.nc.L1::no_allocate.v4.u32 {%0,%1,%2,%3},[%4];" : "=r"(v.x), "=r"(v.y), "=r"(v.z), "=r"(v.w) : "l"(p) : "memory"); return v;
}
__device__ __forceinline__ uint2 lds64(uint32_t a) {
    uint2 v; asm volatile("ld.shared.v2.u32 {%0,%1},[%2];" : "=r"(v.x), "=r"(v.y) : "r"(a) : "memory"); return v;
}
__device__ __forceinline__ void sts32(uint32_t a, uint32_t v) { asm volatile("st.shared.u32 [%0],%1;" ::"r"(a), "r"(v) : "memory"); }
__device__ __forceinline__ void sts64(uint32_t a, uint32_t x, uint32_t y) { asm volatile("st.shared.v2.u32 [%0],{%1,%2};" ::"r"(a), "r"(x), "r"(y) : "memory"); }
__device__ __forceinline__ uint32_t atoms_inc(uint32_t a) {
    uint32_t r; asm volatile("atom.shared.add.u32 %0,[%1],1;" : "=r"(r) : "r"(a) : "memory"); return r;
}
__device__ __forceinline__ uint32_t lds32(uint32_t a) {
    uint32_t v; asm volatile("ld.shared.u32 %0,[%1];" : "=r"(v) : "r"(a) : "memory"); return v;
}

__device__ __noinline__ void generic_path(char* smem, const __nv_bfloat16* __restrict__ x, const __nv_bfloat16* __restrict__ ea,
                                          const int* __restrict__ src, const int* __restrict__ dst,
                                          const __nv_bfloat16* __restrict__ wm, const __nv_bfloat16* __restrict__ wu,
                                          __nv_bfloat16* __restrict__ out) {
    float* agg = (float*)smem;
    __nv_bfloat16* w = (__nv_bfloat16*)(smem + NT * 512);
    int* list = (int*)(smem + NT * 512 + 260 * 256);
    int* cnt = list + NTHR;
    const int tid = threadIdx.x, f = tid & 127, sub = tid >> 7, n0 = first_node(blockIdx.x), nv = first_node(blockIdx.x + 1) - n0;
    __syncthreads();
    for (int i = tid; i < NT * 128; i += NTHR) agg[i] = 0.f;
    for (int i = tid; i < 260 * 128; i += NTHR) w[i] = wm[i];
    for (int base = 0; base < NE; base += NTHR) {
        if (tid == 0) *cnt = 0;
        __syncthreads();
        const int e = base + tid;
        if (e < NE && (unsigned)(dst[e] - n0) < (unsigned)nv) list[atomicAdd(cnt, 1)] = e;
        __syncthreads();
        const int n = *cnt;
        for (int i = sub; i < n; i += NTHR / 128) {
            const int ee = list[i], s = src[ee], d = dst[ee];
            float z = 0.f;
            for (int k = 0; k < 128; k++) {
                z = fmaf(__bfloat162float(x[s * 128 + k]), __bfloat162float(w[k * 128 + f]), z);
                z = fmaf(__bfloat162float(x[d * 128 + k]), __bfloat162float(w[(128 + k) * 128 + f]), z);
            }
            for (int k = 0; k < 4; k++) z = fmaf(__bfloat162float(ea[ee * 4 + k]), __bfloat162float(w[(256 + k) * 128 + f]), z);
            atomicAdd(&agg[(d - n0) * 128 + f], z / (1.f + expf(-z)));
        }
        __syncthreads();
    }
    for (int i = tid; i < 256 * 128; i += NTHR) w[i] = wu[i];
    __syncthreads();
    for (int r = sub; r < nv; r += NTHR / 128) {
        float z = 0.f;
        for (int k = 0; k < 128; k++) {
            z = fmaf(__bfloat162float(x[(n0 + r) * 128 + k]), __bfloat162float(w[k * 128 + f]), z);
            z = fmaf(agg[r * 128 + k], __bfloat162float(w[(128 + k) * 128 + f]), z);
        }
        out[(n0 + r) * 128 + f] = __float2bfloat16(z / (1.f + expf(-z)));
    }
}

__global__ void __launch_bounds__(NTHR, 1)
mpnn_kernel(const __nv_bfloat16* __restrict__ x, const __nv_bfloat16* __restrict__ ea, const int* __restrict__ src,
            const int* __restrict__ dst, const __nv_bfloat16* __restrict__ wm, const __nv_bfloat16* __restrict__ wu,
            __nv_bfloat16* __restrict__ out, char* const scr, const __grid_constant__ CUtensorMap tm_msg,
            const __grid_constant__ CUtensorMap tm_upd, const __grid_constant__ CUtensorMap tm_x, const __grid_constant__ CUtensorMap tm_p,
            const __grid_constant__ CUtensorMap tm_wb) {
    extern __shared__ __align__(1024) char smem[];
    const uint32_t t_start = (uint32_t)clock();
    auto until = [&](uint32_t t) { while ((uint32_t)clock() - t_start < t) {} };
    const uint32_t sb = smem_u32(smem), mb = sb + S_MBAR;
    const int cta = uni(blockIdx.x), n0 = first_node(cta);
    const int nv = first_node(cta + 1) - n0;
    const int n2 = min(CH, NE - cta * CH) >> 1;
    if (threadIdx.x < 128) asm volatile("prefetch.global.L2 [%0];" ::"l"(dst + cta * CH + min((int)threadIdx.x * 32, n2 * 2 - 1)) : "memory");
    if (threadIdx.x == 256) {
        asm volatile("mbarrier.init.shared::cta.b64 [%0],1;" ::"r"(mb + B_DST * 8) : "memory");
        asm volatile("fence.mbarrier_init.release.cluster;" ::: "memory");
        mbar_expect(mb + B_DST * 8, n2 * 8);
        bulk_load(sb + S_Q, dst + cta * CH, n2 * 8, mb + B_DST * 8);
#pragma unroll
        for (int i = 1; i < B_NUM; i++)
            asm volatile("mbarrier.init.shared::cta.b64 [%0],%1;" ::"r"(mb + i * 8), "r"(i >= B_JOIN ? 24 : i >= B_DSFREE ? 12 : i == B_X2FREE ? 4 : 1) : "memory");
        asm volatile("fence.mbarrier_init.release.cluster;" ::: "memory");
    } else if (threadIdx.x < 5) {
        asm volatile("prefetch.tensormap [%0];" ::"l"(threadIdx.x == 0 ? &tm_msg : threadIdx.x == 1 ? &tm_x : threadIdx.x == 2 ? &tm_upd : threadIdx.x == 3 ? &tm_p : &tm_wb) : "memory");
    } else if (threadIdx.x >= 336) {
        ((int*)(smem + S_HIST))[threadIdx.x - 336] = 0;
    }
    const int warp = uni(threadIdx.x >> 5);
    volatile int* misc = (volatile int*)(smem + S_MISC);
    bool bad = false;
    __syncthreads();

    uint32_t tab, qa, qv[4], w[4][4], p[2][2][4], cu[2][2], zero, pLo, pHi;
    auto load_stream = [&]() {
        const int tid = fresh_tid();
        mbar_wait_warp(mb + B_JOIN * 8);
        tab = lds32(sb + S_TAB + (tid >> 4) * 4);
        qa = sb + S_Q + (tid & 15) * LBO + ((tab >> 8) & 0xFF0u);
        const uint4 v = lds128(qa);
        qv[0] = v.x; qv[1] = v.y; qv[2] = v.z; qv[3] = v.w;
    };
    auto ready = [&]() {
        if (bad) misc[0] = 1;
        __syncwarp();
        if (elect()) mbar_arrive(mb + B_READY * 8);
    };
    auto load_w3 = [&]() {
        const int l16 = fresh_tid() & 15;
#pragma unroll
        for (int k0 = 0; k0 < 16; k0++) { const int k = (WPERM >> (4 * k0)) & 15; w[k >> 2][k & 3] = lds32(sb + S_W3 + k * 64 + l16 * 4); }
    };
    auto gather = [&](uint32_t(&d)[4], uint32_t m, uint32_t dep) {
        uint32_t hi;
        uint64_t a;
        asm("lop3.b32 %0,%1,%2,%3,0xF8;" : "=r"(hi) : "r"(pHi), "r"(dep), "r"(zero));
        asm("mov.b64 %0,{%1,%2};" : "=l"(a) : "r"(prmt(m, pLo, 0x7324)), "r"(hi));
        asm volatile("ld.relaxed.gpu.global.v4.u32 {%0,%1,%2,%3},[%4];" : "=r"(d[0]), "=r"(d[1]), "=r"(d[2]), "=r"(d[3]) : "l"(a) : "memory");
    };
    auto first_rows = [&]() {
        const uint4 m = lds128(sb + S_RM + (tab & 0xFFFu) * 4);
        cu[0][0] = m.x; cu[0][1] = m.y; cu[1][0] = m.z; cu[1][1] = m.w;
        zero = tab >> 31;
        pLo = (uint32_t)(uintptr_t)scr + (fresh_tid() & 15) * 16 + zero;
        pHi = (uint32_t)((uintptr_t)scr >> 32);
        mbar_wait_warp(mb + B_GO * 8);
#pragma unroll
        for (int i = 0; i < 4; i++) gather(p[i >> 1][i & 1], cu[i >> 1][i & 1], zero);
    };

    if (warp < 12) {
        asm volatile("setmaxnreg.inc.sync.aligned.u32 96;");
        int tid = fresh_tid(), lane = tid & 31;
        const int wg = warp >> 2;
        if (tid == 256) {
            auto load_w = [&](int b, const CUtensorMap* tm, int row, int s0, int s1) {
                mbar_expect(mb + b * 8, 32768);
                tma_load(sb + s0, tm, row, 0, mb + b * 8);
                tma_load(sb + s1, tm, row, 1, mb + b * 8);
            };
            auto load_x = [&](int k) {
                mbar_expect(mb + (B_X + k) * 8, 16384);
                tma_load(sb + (k < 2 ? S_U + k * 16384 : S_Q), &tm_x, n0 + k * 64, 0, mb + (B_X + k) * 8);
            };
            until(T_SRC);
            mbar_expect(mb + B_SRC * 8, n2 * 8);
            bulk_load(sb + S_RAWS, src + cta * CH, n2 * 8, mb + B_SRC * 8);
            until(T_W1); load_w(B_W1, &tm_msg, 0, S_U + 32768, S_WB);
            until(T_X0); load_x(0);
            until(T_WT); load_w(B_WT, &tm_upd, 0, S_WB + 16384, S_WX);
            until(T_W2); load_w(B_W2, &tm_msg, 128, S_WX + 16384, S_WX + 32768);
            until(T_X1); load_x(1);
            until(T_X2);
            mbar_wait(mb + B_DSFREE * 8);
            fence_async();
            load_x(2);
        }
        if (wg == 1) {
            const int t = tid & 127;
            uint32_t wmax = 0;
#pragma unroll
            for (int k = 0; k < 4; k++) {
                const uint32_t w = ((const uint16_t*)wm)[(256 + k) * 128 + t];
                wmax = max(wmax, w & 0x7fffu);
                *(__half*)(smem + S_W3 + k * 256 + (t & 6) * 32 + (t >> 3) * 4 + (t & 1) * 2) = __float2half_rn(0.5f * __uint_as_float(w << 16));
            }
            bad = wmax >= 0x4300u || !__any_sync(0xffffffffu, wmax >= 0x3B00u);
        } else if (warp == 0) {
            uint4 v = ldg128((const uint4*)wu + (128 + ((cta + (lane < 16 ? 64 : 0)) & 127)) * 16 + (lane & 15));
            bad = !__any_sync(0xffffffffu, mag16(amax_bf2(amax_bf2(v.x, v.y), amax_bf2(v.z, v.w))) >= 0x3C00u);
            v = make_uint4(bf2_to_h2(half_bf2(v.x)), bf2_to_h2(half_bf2(v.y)), bf2_to_h2(half_bf2(v.z)), bf2_to_h2(half_bf2(v.w)));
            if (lane < 16) v = make_uint4(0xFBFFFBFFu, 0xFBFFFBFFu, 0xFBFFFBFFu, 0xFBFFFBFFu);
            *(uint4*)(scr + (lane < 16 ? G_P + (NULLROW + cta) * 256 : G_WB + cta * 256) + (lane & 15) * 16) = v;
        }
        __syncwarp();
        mbar_wait_warp(mb + (B_X + wg) * 8);
        const uint32_t ua = sb + S_U + wg * 16384 + ((warp & 3) * 16 + (lane & 15)) * 128 + (((lane >> 4) ^ (lane & 7)) << 4);
        uint32_t xa[8][4];
#pragma unroll
        for (int ks = 0; ks < 8; ks++) ldsm4(xa[ks], (ua ^ ((ks & 3) << 5)) + (ks >> 2) * 8192 + (wg < 2 ? 0 : S_Q - S_U - 32768));
#pragma unroll
        for (int i = 0; i < 32; i++) xa[i >> 2][i & 3] = half_bf2(xa[i >> 2][i & 3]);
        mbar_wait_warp(mb + B_W1 * 8);

        float d[32];
        uint32_t v[16];
        gemm_half(d, xa, sb + S_U + 32768);
#pragma unroll
        for (int hh = 0; hh < 5; hh++) {
            gemm_wait(d);
#pragma unroll
            for (int i = 0; i < 16; i++) v[i] = (hh >> 1) == 1 ? pack_bf(d[2 * i], d[2 * i + 1]) : pack_h(d[2 * i], d[2 * i + 1]);
            auto next = [&]() {
                if (hh == 1 || hh == 3) mbar_wait_warp(mb + (hh == 1 ? B_WT : B_W2) * 8);
                gemm_half(d, xa, sb + (hh < 2 ? S_WB + hh * 16384 : S_WX + (hh - 2) * 16384));
            };
            if (hh != 1) next();
            if (hh == 0) {
                if (wg == 2) { if (lane == 0) mbar_arrive(mb + B_X2FREE * 8); bar_sync(2, 384); }
                else bar_arrive(2, 384);
            }
            if (hh < 4) {
#pragma unroll
                for (int c = 0; c < 4; c++) stsm4((ua ^ (c << 5)) + (hh & 1) * 8192, v[4 * c], v[4 * c + 1], v[4 * c + 2], v[4 * c + 3]);
            }
            if (hh < 2) {
                fence_async();
                __syncwarp();
                if (lane == 0) tma_store(&tm_p, sb + S_U + wg * 16384 + hh * 8192 + (warp & 3) * 2048, n0 + warp * 16, hh);
                __syncwarp();
            }
            if (hh == 1) {
                next();
                if (lane == 0) { bulk_wait(); mbar_arrive(mb + B_PDONE * 8); }
                __syncwarp();
            }
        }
        uint32_t v1[16];
        gemm_wait(d);
        tid = fresh_tid(); lane = tid & 31;
#pragma unroll
        for (int i = 0; i < 16; i++) v1[i] = pack_h(d[2 * i], d[2 * i + 1]);
        if (warp == 1) {
            mbar_wait(mb + B_EFREE * 8);
            fence_async();
            if (lane == 0) { bulk_store(scr + G_RE + cta * CHP * 8, sb + S_RE, n2 * 16); }
            __syncwarp();
        }
        if (warp == 0) {
            mbar_wait(mb + B_PDONE * 8);
            if (lane == 0) { grid_arrive(scr, cta); }
            __syncwarp();
        } else if (warp == 1) {
            if (lane == 0) { bulk_wait(); mbar_arrive(mb + B_ESENT * 8); }
            __syncwarp();
        }
        mbar_wait(mb + B_EFREE * 8);
        mbar_wait_warp(mb + B_X2FREE * 8);
        const uint32_t qs = sb + S_Q + (lane >> 4) * LBO + (warp * 16 + (lane & 15) + 1) * 16;
#pragma unroll
        for (int c = 0; c < 4; c++) {
            stsm4(qs + 2 * c * LBO, v[4 * c], v[4 * c + 1], v[4 * c + 2], v[4 * c + 3]);
            stsm4(qs + (8 + 2 * c) * LBO, v1[4 * c], v1[4 * c + 1], v1[4 * c + 2], v1[4 * c + 3]);
        }
        if (warp >= 2) {
            if (warp >= 4) mbar_wait(mb + B_ESENT * 8);
            mbar_wait_warp(mb + B_SCAN * 8);
            const uint2 mi = lds64(sb + S_MISC + 8);
            const int total = mi.x, t = tid - 64;
            uint32_t pz = 0;
            if (warp < 4) {
                const int T = (total + 32) >> 5, w6 = t >> 3;
                const int b = T / 6, rem = T - b * 6;
                const int L = (b + (w6 >= 6 - rem)) * 4, pos = (b * w6 + max(w6 + rem - 6, 0)) * 32 + (t & 7) * L;
                const uint32_t pa = sb + S_RM + pos * 4;
                auto st = [&](int i) { return lds32(sb + S_ST + ((n0 + i) & 255) * 4); };
                int cnt = st(127) < pa ? 64 : 0;
#pragma unroll
                for (int o = 64; o > 0; o >>= 1) cnt += st(cnt + o - 1) < pa ? o : 0;
                cnt += st(cnt) < pa;
                if (t < 48) sts32(sb + S_TAB + t * 4, pos | (min(cnt, nv + 1) << 12) | (L << 20));
            } else if (warp < 6) {
                if (total >= 0) pz = sb + S_RM + (total + t - 64) * 4;
            } else if (mi.y) {
                const uint32_t i = ((n0 + t - 128) & 255) * 4;
                if (t - 128 < nv && lds32(sb + S_H2 + i) == 0) pz = lds32(sb + S_ST + i);
            }
            if (pz) {
                sts32(pz, ((uint32_t)(NULLROW + cta) << 16) | (t > 64 && t < 128));
                sts64(pz * 2 - (sb + (2 * S_RM - S_RE)), 0, 0);
            }
            __syncwarp();
        }
        const uint32_t mx = amax_h2(amax_h2(amax_h2(v[0], v[2]), amax_h2(v[4], v[6])), amax_h2(amax_h2(v[8], v[10]), amax_h2(v[12], v[14])));
        bad |= warp * 16 < nv && !__any_sync(0xffffffffu, mag16(mx) >= 0x2400u);
        if (lane == 0) mbar_arrive(mb + B_JOIN * 8);
        asm volatile("setmaxnreg.dec.sync.aligned.u32 80;");
        mbar_wait_warp(mb + B_PDONE * 8);
        load_w3();
        if (warp == 0) {
            bad |= grid_wait(scr, misc[1], lane);
            if (lane == 0) { mbar_arrive(mb + B_GO * 8); }
        }
        load_stream();
        ready();
        first_rows();
    } else {
        asm volatile("setmaxnreg.dec.sync.aligned.u32 64;");
        const int t = opaque(threadIdx.x - 384), lane = t & 31, ew = warp - 12;
        const uint32_t tag = (ld_rlx(scr + G_CNT + (cta & 7) * 128) >> 5) + 1;
        const uint32_t glo = (uint32_t)(uintptr_t)scr, ghi = (uint32_t)((uintptr_t)scr >> 32);
        const uint32_t e_s = sb + (2 * S_RM - S_RE), e_g = glo + (2 * G_RM - G_RE);
        const uint32_t ra = sb + S_Q + t * 8, ra3 = sb + S_Q + min(t + 1152, n2 - 1) * 8;
        mbar_wait_warp(mb + B_DST * 8);
        uint32_t dv[8], ba[8], ps[8];
#pragma unroll
        for (int k = 0; k < 4; k++) { const uint2 v = lds64(k < 3 ? ra + 3072 * k : ra3); dv[2 * k] = v.x * 4; dv[2 * k + 1] = v.y * 4; }
#pragma unroll
        for (int i = 0; i < 8; i++) {
            ba[i] = ((dv[i] * OWN) >> 24) * 4 + sb;
            if (i >= 6) ba[i] = t + 1152 < n2 ? ba[i] : sb + 135 * 4;
            ps[i] = atoms_inc(ba[i] + S_HIST);
        }
        bar_sync(5, 384);
        if (ew == 11) {
            int c[5], s = 0;
#pragma unroll
            for (int i = 0; i < 5; i++) { c[i] = lds32(sb + S_HIST + lane * 20 + i * 4); s += c[i]; }
            int inc = s;
#pragma unroll
            for (int o = 1; o < 32; o <<= 1) { const int v = __shfl_up_sync(0xffffffffu, inc, o); if (lane >= o) inc += v; }
            inc -= s;
#pragma unroll
            for (int i = 0; i < 5; i++) {
                sts32(sb + S_OFA + lane * 20 + i * 4, sb + S_RM + inc * 4);
                sts32(sb + S_ENT + lane * 20 + i * 4, inc | (c[i] << 12) | (tag << 24));
                inc += c[i];
            }
            misc[1] = tag;
        }
        bar_sync(5, 384);
        if (t == 352) { fence_async(); bulk_store(scr + G_OFF + cta * OFFS * 4, sb + S_ENT, OFFS * 4); }
        __syncwarp();
#pragma unroll
        for (int i = 0; i < 8; i++) ps[i] = ps[i] * 4 + lds32(ba[i] + S_OFA);
        mbar_wait_warp(mb + B_SRC * 8);
        const uint32_t tg = (tag & 63) << 10;
#pragma unroll
        for (int k = 0; k < 4; k++) { const uint2 v = lds64((k < 3 ? ra + 3072 * k : ra3) + 16384); ba[2 * k] = v.x; ba[2 * k + 1] = v.y; }
#pragma unroll
        for (int i = 0; i < 8; i++) sts32(ps[i], (dv[i] & 0x3FCu) | (ba[i] * 65536u + tg));
#pragma unroll
        for (int i = 0; i < 8; i++) asm volatile("mad.lo.u32 %0,%0,2,%1;" : "+r"(ps[i]) : "r"(0u - e_s));
        __syncwarp();
        if (lane == 0) mbar_arrive(mb + B_DSFREE * 8);
        mbar_wait_warp(mb + B_DSFREE * 8);
        if (t == 0) { fence_async(); bulk_store(scr + G_RM + cta * CHP * 4, sb + S_RM, n2 * 8); bulk_commit(); }
        __syncwarp();
        until(T_OFF);
        uint32_t m[12], ga[12];
        {
            const int c = ew * 11 + min(lane, 10);
            uint32_t ent;
            int it = 0;
#pragma unroll 1
            do { ent = ld_rlx(scr + G_OFF + (c * OFFS + cta) * 4); } while (__any_sync(0xffffffffu, ((ent >> 24) ^ tag) & 0xFF) && ++it < SPIN);
            if (it >= SPIN) { bad = true; ent = 0; }
            const uint32_t beg = glo + G_RM + (c * CHP + (ent & 0xFFF)) * 4, end = beg + ((ent >> 10) & 0x3FFC);
            sts64(sb + S_OFA + c * 8, beg, end);
            uint32_t more = __ballot_sync(0xffffffffu, end - beg > 128) & 0x7FFu, used = 0;
            ga[11] = 0;
#pragma unroll 1
            while (more) {
                const uint2 v = lds64(sb + S_OFA + (ew * 11 + __ffs(more) - 1) * 8);
                if (lane * 4 >= used) ga[11] = v.x + 128 + lane * 4 - used;
                used += v.y - v.x - 128;
                more &= more - 1;
            }
            bad |= used > 128;
            until(T_REC);
            const uint32_t idle = (((n0 + 192 + lane) & 255) << 2) | tg;
            auto load = [&]() {
#pragma unroll
                for (int r = 0; r < 12; r++) {
                    uint32_t lhs = lane * 4, rhs = used;
                    if (r < 11) { const uint2 v = lds64(sb + S_OFA + (ew * 11 + r) * 8); lhs = ga[r] = v.x + lane * 4; rhs = v.y; }
                    m[r] = idle;
                    asm volatile("{.reg .pred p; .reg .b64 a; setp.lt.u32 p,%3,%4; mov.b64 a,{%1,%2}; @p ld.relaxed.gpu.global.u32 %0,[a];}"
                                 : "+r"(m[r]) : "r"(ga[r]), "r"(ghi), "r"(lhs), "r"(rhs) : "memory");
                }
            };
            auto stale = [&]() {
                uint32_t df = 0;
#pragma unroll
                for (int r = 0; r < 12; r += 4) df |= ((m[r] ^ tg) | (m[r + 1] ^ tg)) | ((m[r + 2] ^ tg) | (m[r + 3] ^ tg));
                return __any_sync(0xffffffffu, df & 0xFC00u);
            };
            it = 0;
#pragma unroll 1
            do {
                load();
                if (ew == 11 && it == 0) {
#pragma unroll 1
                    for (int k = 0; k < 2; k++) {
                        until(k ? T_E1 : T_E0);
                        if (lane == 0) {
                            mbar_expect(mb + (B_E0 + k) * 8, k ? n2 * 16 - 12288 : 12288);
                            bulk_load(sb + S_RAWE + k * 12288, ea + cta * CH * 4 + k * 6144, k ? n2 * 16 - 12288 : 12288, mb + (B_E0 + k) * 8);
                        }
                        __syncwarp();
                    }
                }
            } while (stale() && ++it < SPIN);
            bad |= it >= SPIN;
        }
        uint32_t rk[12];
#pragma unroll
        for (int r = 0; r < 12; r++) rk[r] = atoms_inc(sb + S_H2 + (m[r] & 0x3FCu));
#pragma unroll
        for (int r = 0; r < 12; r++) asm volatile("" : "+r"(m[r]));
        auto stage_e = [&]() {
#pragma unroll
            for (int b = 0; b < 2; b++) {
                mbar_wait_warp(mb + (b ? B_E : B_E0) * 8);
                uint4 u[2];
#pragma unroll
                for (int k = 0; k < 2; k++) u[k] = lds128((2 * b + k < 3 ? ra + 3072 * (2 * b + k) : ra3) * 2 - (sb + (2 * S_Q - S_RAWE)));
#pragma unroll
                for (int k = 0; k < 2; k++) {
                    sts64(ps[4 * b + 2 * k], put_tag(bf2_to_h2(u[k].x), tag), bf2_to_h2(u[k].y));
                    sts64(ps[4 * b + 2 * k + 1], put_tag(bf2_to_h2(u[k].z), tag), bf2_to_h2(u[k].w));
                }
            }
            __syncwarp();
            if (lane == 0) mbar_arrive(mb + B_EFREE * 8);
        };
        stage_e();
        bar_sync(5, 384);
        if (ew == 0) {
            if (lane == 0) asm volatile("cp.async.bulk.wait_group.read 0;" ::: "memory");
            __syncwarp();
        } else if (ew == 11) {
            int c[6], s = 0, cm = 0;
            bool z = false;
#pragma unroll
            for (int i = 0; i < 6; i++) {
                c[i] = lds32(sb + S_H2 + ((n0 + lane * 6 + i) & 255) * 4);
                if (lane * 6 + i < nv) { z |= c[i] == 0; c[i] = max(c[i], 1); }
                s += c[i];
                cm = max(cm, c[i]);
            }
            int inc = s;
#pragma unroll
            for (int o = 1; o < 32; o <<= 1) { const int v = __shfl_up_sync(0xffffffffu, inc, o); if (lane >= o) inc += v; }
            const int total = __shfl_sync(0xffffffffu, inc, 31);
            const bool over = __any_sync(0xffffffffu, cm > 256) || total + 64 > RCAP;
            inc -= s;
#pragma unroll
            for (int i = 0; i < 6; i++) { sts32(sb + S_ST + ((n0 + lane * 6 + i) & 255) * 4, over ? 0 : sb + S_RM + inc * 4); inc += c[i]; }
            sts32(sb + S_ST + ((n0 + 192 + lane) & 255) * 4, 0);
            sts32(sb + S_ST + ((n0 + 224 + lane) & 255) * 4, 0);
            sts64(sb + S_MISC + 8, over ? -1 : total, __any_sync(0xffffffffu, z));
            bad |= over;
        }
        bar_sync(5, 384);
        if (t == 0) { mbar_arrive(mb + B_SCAN * 8); }
#pragma unroll
        for (int r = 0; r < 12; r++) {
            const uint32_t st = lds32(sb + S_ST + (m[r] & 0x3FCu));
            m[r] = prmt(rk[r], m[r], 0x7610);
            rk[r] = rk[r] * 4 + st;
        }
#pragma unroll
        for (int r = 0; r < 12; r++)
            asm volatile("{.reg .pred p; setp.ge.u32 p,%0,%2; @p st.shared.u32 [%0],%1;}" ::"r"(rk[r]), "r"(m[r]), "n"(S_RM) : "memory");
        __syncwarp();
        if (lane == 0) mbar_arrive(mb + B_JOIN * 8);
        const uint32_t dump = sb + S_HIST + lane * 8;
#pragma unroll
        for (int r = 0; r < 12; r++) rk[r] = min(rk[r] * 2 - e_s, dump);
        until(T_ER + cta * 6);
        {
            bool again;
            int it = 0;
#pragma unroll 1
            do {
                uint2 ee[12];
                uint32_t df = 0;
#pragma unroll
                for (int r = 0; r < 12; r++) {
                    const uint32_t a = r < 11 ? lds32(sb + S_OFA + (ew * 11 + r) * 8) * 2 + (lane * 8 - e_g) : ga[r] * 2 - e_g;
                    ee[r].x = tag;
                    asm volatile("{.reg .pred p; .reg .b64 a; setp.lt.u32 p,%4,%5; mov.b64 a,{%2,%3}; @p ld.relaxed.gpu.global.v2.u32 {%0,%1},[a];}"
                                 : "+r"(ee[r].x), "=r"(ee[r].y) : "r"(a), "r"(ghi), "r"(rk[r]), "r"(S_HIST - (it & 1)) : "memory");
                }
                load_stream();
#pragma unroll
                for (int r = 0; r < 12; r++) { ee[r].x ^= tag & 3; sts64(rk[r], ee[r].x, ee[r].y); df |= ee[r].x; }
                again = __any_sync(0xffffffffu, df & 3u);
            } while (again && ++it < SPIN);
            bad |= again;
        }
        ready();
        asm volatile("setmaxnreg.inc.sync.aligned.u32 80;");
        first_rows();
        load_w3();
    }

    uint32_t e[2][4], h[2][4] = {}, acc[4] = {0, 0, 0, 0};
    const uint32_t mp = sb + S_RM + (tab & 0xFFFu) * 4, ep = sb + S_RE + (tab & 0xFFFu) * 8;
    const uint32_t qa0 = qa;
    auto lde = [&](uint32_t(&d)[4], uint32_t a) { const uint4 v = lds128(a); d[0] = v.x; d[1] = v.y; d[2] = v.z; d[3] = v.w; };
    auto stage_a = [&](uint32_t(&o)[4], const uint32_t(&pr)[4], uint32_t e01, uint32_t e23) {
        const __half2 e0 = __low2half2(H2(e01)), e1 = __high2half2(H2(e01)), e2 = __low2half2(H2(e23)), e3 = __high2half2(H2(e23));
#pragma unroll
        for (int j = 0; j < 4; j++)
            o[j] = U32(__hfma2(e3, H2(w[3][j]), __hfma2(e2, H2(w[2][j]), __hfma2(e1, H2(w[1][j]), __hfma2(e0, H2(w[0][j]), H2(pr[j]))))));
    };
    uint32_t um = 0, ue = 0;
    auto blk = [&](auto S, auto I, auto LAST) {
        constexpr int s = S.value, i = I.value;
        constexpr bool last = LAST.value;
        const bool first = (cu[s][i] & 0x1FFu) == 0;
        if (__any_sync(0xffffffffu, first)) {
            if (first) {
                qa += 16;
                lde(qv, qa);
                sts128(qa, acc[0], acc[1], acc[2], acc[3]);
#pragma unroll
                for (int j = 0; j < 4; j++) acc[j] = h[i][j] & zero;
            }
            __syncwarp();
        }
        if (i == 0 && !last) {
            asm volatile("{.reg .u32 a; add.u32 a,%4,%5; ld.shared.v4.u32 {%0,%1,%2,%3},[a+%6];}"
                         : "=r"(e[s ^ 1][0]), "=r"(e[s ^ 1][1]), "=r"(e[s ^ 1][2]), "=r"(e[s ^ 1][3]) : "r"(ep), "r"(ue), "n"((s + 1) * 16) : "memory");
        } else if (!last) {
            asm volatile("{.reg .u32 a; add.u32 a,%2,%3; ld.shared.v2.u32 {%0,%1},[a+%4];}"
                         : "=r"(cu[s][0]), "=r"(cu[s][1]) : "r"(mp), "r"(um), "n"((s + 2) * 8) : "memory");
            gather(p[s][0], cu[s][0], p[s ^ 1][1][0]);
            gather(p[s][1], cu[s][1], p[s ^ 1][1][1]);
        }
        if (i == 0) stage_a(h[1], p[s][1], e[s][2], e[s][3]);
        else if (!last || s == 0) stage_a(h[0], p[s ^ 1][0], e[s ^ 1][0], e[s ^ 1][1]);
#pragma unroll
        for (int j = 0; j < 4; j++) {
            const __half2 t = __hadd2(H2(h[i][j]), H2(qv[j]));
            acc[j] = U32(__hadd2(H2(acc[j]), __hfma2(t, H2(tanh_h2(U32(t))), t)));
        }
    };
    using C0 = std::integral_constant<int, 0>;
    using C1 = std::integral_constant<int, 1>;
    mbar_wait_warp(mb + B_READY * 8);
    lde(e[0], ep);
    const int L = uni(misc[0] ? -1 : (int)(tab >> 20));
    if (L < 0) {
        generic_path(smem, x, ea, src, dst, wm, wu, out);
        return;
    }
    stage_a(h[0], p[0][0], e[0][0], e[0][1]);
    if (L > 0) {
        blk(C0{}, C0{}, C0{});
#pragma unroll 1
        for (int it = 4; it < L; it += 4) {
            blk(C0{}, C1{}, C0{}); blk(C1{}, C0{}, C0{}); blk(C1{}, C1{}, C0{});
            um += 16; ue += 32;
            blk(C0{}, C0{}, C0{});
        }
        blk(C0{}, C1{}, C1{});
        if (warp == 20 && elect()) {
            asm volatile("fence.proxy.async.global;" ::: "memory");
            mbar_expect(mb + B_WB * 8, 32768);
            tma_load(sb + S_WB, &tm_wb, 0, 0, mb + B_WB * 8);
        }
        blk(C1{}, C0{}, C1{}); blk(C1{}, C1{}, C1{});
    }

    {
    const int lane = fresh_tid() & 31, l16 = lane & 15, n0 = first_node(fresh_cta()), nv = first_node(fresh_cta() + 1) - n0;
    const int tile = warp >> 3, half = (warp >> 2) & 1, g = lane >> 2;
    const int r0 = tile * 64 + (warp & 3) * 16;
    float d[32];
    const uint32_t ub = sb + S_U + (warp >> 2) * 8192 + (warp & 3) * 2048;
    const uint32_t ua = ub + (lane & 15) * 128 + (((lane >> 4) ^ (lane & 7)) << 4);
#pragma unroll
    for (int c = 0; c < 4; c++) {
        uint32_t u[4];
        ldsm4(u, ua ^ (c << 5));
#pragma unroll
        for (int i = 0; i < 4; i++) { d[8 * c + 2 * i] = __uint_as_float(u[i] << 16); d[8 * c + 2 * i + 1] = __uint_as_float(u[i] & 0xffff0000u); }
    }
    const bool live = qa < sb + S_Q + l16 * LBO + (nv + 1) * 16;
    const bool shared_target = __syncthreads_or(live && qa == qa0);
    if (shared_target) {
#pragma unroll
        for (int j = 0; j < 4; j++) asm volatile("red.shared.add.noftz.f16x2 [%0],%1;" ::"r"(qa + 16 + j * 4), "r"(acc[j]) : "memory");
    } else if (live) {
        const uint4 v = lds128(qa + 16);
        sts128(qa + 16, U32(__hadd2(H2(v.x), H2(acc[0]))), U32(__hadd2(H2(v.y), H2(acc[1]))), U32(__hadd2(H2(v.z), H2(acc[2]))), U32(__hadd2(H2(v.w), H2(acc[3]))));
    }
    fence_async();
    if (warp == 20) mbar_wait_warp(mb + B_WB * 8);
    __syncthreads();
    {
        const uint64_t da = ((uint64_t)8 << 32) | ((uint64_t)(LBO >> 4) << 16) | (uint64_t)(((sb + S_Q + (tile * 64 + 2) * 16) & 0x3FFFF) >> 4);
        const uint64_t db = ((uint64_t)1 << 62) | ((uint64_t)64 << 32) | ((uint64_t)1 << 16) | (uint64_t)(((sb + S_WB + half * 16384) & 0x3FFFF) >> 4);
        if (warp >= 4) bar_sync(7 + (warp >> 2), 256);
        asm volatile("wgmma.fence.sync.aligned;" ::: "memory");
#pragma unroll
        for (int ks = 0; ks < 8; ks++)
            asm volatile(
                "wgmma.mma_async.sync.aligned.m64n64k16.f32.f16.f16 "
                "{%0,%1,%2,%3,%4,%5,%6,%7,%8,%9,%10,%11,%12,%13,%14,%15,%16,%17,%18,%19,%20,%21,%22,%23,%24,%25,%26,%27,%28,%29,%30,%31},"
                "%32,%33,1,1,1,0,1;"
                : "+f"(d[0]), "+f"(d[1]), "+f"(d[2]), "+f"(d[3]), "+f"(d[4]), "+f"(d[5]), "+f"(d[6]), "+f"(d[7]),
                  "+f"(d[8]), "+f"(d[9]), "+f"(d[10]), "+f"(d[11]), "+f"(d[12]), "+f"(d[13]), "+f"(d[14]), "+f"(d[15]),
                  "+f"(d[16]), "+f"(d[17]), "+f"(d[18]), "+f"(d[19]), "+f"(d[20]), "+f"(d[21]), "+f"(d[22]), "+f"(d[23]),
                  "+f"(d[24]), "+f"(d[25]), "+f"(d[26]), "+f"(d[27]), "+f"(d[28]), "+f"(d[29]), "+f"(d[30]), "+f"(d[31])
                : "l"(da + ks * (2 * LBO >> 4)), "l"(db + ks * 128));
        asm volatile("wgmma.commit_group.sync.aligned;" ::: "memory");
        if (warp < 20) bar_arrive(8 + (warp >> 2), 256);
        asm volatile("wgmma.wait_group.sync.aligned 0;" ::: "memory");
#pragma unroll
        for (int i = 0; i < 32; i++) asm volatile("" : "+f"(d[i])::"memory");
    }
    bad = (r0 + g < nv && !(fabsf(d[0]) < 3e38f)) || (r0 + g + 8 < nv && !(fabsf(d[2]) < 3e38f));
    if (r0 == 0) {
        float sum = 0.f;
#pragma unroll
        for (int i = 0; i < 8; i++) sum += d[4 * i] * 0.f + d[4 * i + 1] * 0.f;
        bad |= !(sum == 0.f);
    }
    {
        const uint32_t sa = ub + (lane & 7) * 128 + (((lane >> 3) ^ (lane & 7)) << 4);
        uint4* op = (uint4*)out + (n0 + r0 + (lane >> 3)) * 16 + half * 8 + (lane & 7);
#pragma unroll
        for (int rr = 0; rr < 2; rr++) {
#pragma unroll
            for (int c = 0; c < 2; c++) {
                uint32_t o[4];
#pragma unroll
                for (int i = 0; i < 4; i++) {
                    const float a = d[16 * c + 4 * i + 2 * rr], b = d[16 * c + 4 * i + 2 * rr + 1];
                    o[i] = pack_bf(fmaf(a, tanh_f(a), a), fmaf(b, tanh_f(b), b));
                }
                stsm4((sa ^ (c << 6)) + rr * 1024, o[0], o[1], o[2], o[3]);
            }
            __syncwarp();
#pragma unroll
            for (int k = 2 * rr; k < 2 * rr + 2; k++) {
                const int row = k * 4 + (lane >> 3);
                const uint4 v = lds128(ub + row * 128 + (((lane ^ row) & 7) << 4));
                if (r0 + row < nv) op[k * 64] = v;
            }
        }
    }
    }
    if (__syncthreads_or(bad)) generic_path(smem, x, ea, src, dst, wm, wu, out);
}

}

typedef CUresult (*EncodeFn)(CUtensorMap*, CUtensorMapDataType, cuuint32_t, void*, const cuuint64_t*, const cuuint64_t*, const cuuint32_t*,
                             const cuuint32_t*, CUtensorMapInterleave, CUtensorMapSwizzle, CUtensorMapL2promotion, CUtensorMapFloatOOBfill);

static void encode_rows(EncodeFn fn, CUtensorMap* tm, void* p, int rows, int box_rows, int box_halves) {
    const cuuint64_t dims[3] = {64, (cuuint64_t)rows, 2};
    const cuuint64_t strides[2] = {256, 128};
    const cuuint32_t box[3] = {64, (cuuint32_t)box_rows, (cuuint32_t)box_halves}, es[3] = {1, 1, 1};
    fn(tm, CU_TENSOR_MAP_DATA_TYPE_BFLOAT16, 3, p, dims, strides, box, es, CU_TENSOR_MAP_INTERLEAVE_NONE, CU_TENSOR_MAP_SWIZZLE_128B,
       CU_TENSOR_MAP_L2_PROMOTION_L2_256B, CU_TENSOR_MAP_FLOAT_OOB_FILL_NONE);
}

extern "C" void kernel_launch(void* const* d_in, const int* in_sizes, int n_in, void* d_out, int out_size) {
    (void)in_sizes; (void)n_in; (void)out_size;
    static EncodeFn encode = nullptr;
    static void* pbase = nullptr;
    if (!encode) {
        cudaFuncSetAttribute(mpnn_kernel, cudaFuncAttributeMaxDynamicSharedMemorySize, S_TOTAL);
        void* fn = nullptr;
        cudaDriverEntryPointQueryResult qr;
        cudaGetDriverEntryPoint("cuTensorMapEncodeTiled", &fn, cudaEnableDefault, &qr);
        encode = (EncodeFn)fn;
        cudaGetSymbolAddress(&pbase, g_scratch);
        pbase = (void*)(((uintptr_t)pbase + 0xFFFFFFull) & ~(uintptr_t)0xFFFFFFull);
    }
    CUtensorMap tm_msg, tm_upd, tm_x, tm_p, tm_wb;
    encode_rows(encode, &tm_msg, d_in[4], 256, 128, 1);
    encode_rows(encode, &tm_upd, d_in[5], 256, 128, 1);
    encode_rows(encode, &tm_x, d_in[0], NN, 64, 2);
    encode_rows(encode, &tm_p, pbase, NULLROW, 16, 1);
    encode_rows(encode, &tm_wb, (char*)pbase + G_WB, 128, 128, 2);
    mpnn_kernel<<<NCTA, NTHR, S_TOTAL, cudaStreamPerThread>>>(
        (const __nv_bfloat16*)d_in[0], (const __nv_bfloat16*)d_in[1], (const int*)d_in[2], (const int*)d_in[3],
        (const __nv_bfloat16*)d_in[4], (const __nv_bfloat16*)d_in[5], (__nv_bfloat16*)d_out, (char*)pbase, tm_msg, tm_upd, tm_x, tm_p, tm_wb);
}
```
